```python
import torch

def _softmax(x, axis=-1):
    return torch.softmax(x, dim=axis)
def _gelu(x):
    return torch.nn.functional.gelu(x, approximate="tanh")
def _silu(x):
    return torch.nn.functional.silu(x)
def _sigmoid(x):
    return torch.sigmoid(x)
def _layernorm(x, axis=-1, eps=1e-5):
    m = x.mean(dim=axis, keepdim=True)
    v = x.var(dim=axis, keepdim=True, unbiased=False)
    return (x - m) / torch.sqrt(v + eps)
def _scatter_add(tgt, idx, src, axis=0):
    return tgt.clone().index_add_(axis, idx, src)
def _segment_sum(src, seg, n):
    out = torch.zeros((n,) + src.shape[1:], dtype=src.dtype)
    return out.index_add_(0, seg, src)
def _pad(x, pw):
    flat = tuple(v for pair in reversed(pw) for v in pair)
    return torch.nn.functional.pad(x, flat)

kernel_name = 'gated_mix__sliding_block_cached__dense_activation_mish__decode'

def setup_inputs():

    _w = (lambda a: (lambda t: t.to(torch.bfloat16) if t.is_floating_point() else t)(torch.as_tensor(a)))
    def _A_setup():
        B, Sq, D = 4, 1, 512
        Hq, Hkv, Sk, Dh = 32, 8, 4096, 128
        assert Hq % Hkv == 0, (Hq, Hkv)
        return {
            "x": _w((lambda *s: torch.randn(*s, dtype=torch.bfloat16) * 0.05)(B, Sq, D)),
            "k_cache": _w((lambda *s: torch.randn(*s, dtype=torch.bfloat16) * 6.4)(B, Hkv, Sk, Dh)),
            "v_cache": _w((lambda *s: torch.randn(*s, dtype=torch.bfloat16) * 0.1)(B, Hkv, Sk, Dh)),
            "wq": _w((lambda *s: torch.randn(*s, dtype=torch.bfloat16) * 6.4)(D, Hq * Dh) * (D ** -0.5)),
            "wo": _w((lambda *s: torch.randn(*s, dtype=torch.bfloat16) * 0.1)(Hq * Dh, D) * ((Hq * Dh) ** -0.5)),
        }
    _A_in = _A_setup()

    def _B_setup():
        B, S, D, F = 4, 1, 512, 1792
        return {
            "x": _w((lambda *s: torch.randn(*s, dtype=torch.bfloat16) * 0.05)(B, S, D)),
            "w1": _w((lambda *s: torch.randn(*s, dtype=torch.bfloat16) * 3.2)(D, F) * (D ** -0.5)),
            "b1": _w((lambda *s: torch.randn(*s, dtype=torch.bfloat16) * 0.1)(F)),
            "w2": _w((lambda *s: torch.randn(*s, dtype=torch.bfloat16) * 0.1)(F, D) * (F ** -0.5)),
        }
    _B_in = _B_setup()

    return {
        "A_x": _A_in["x"],
        "A_k_cache": _A_in["k_cache"],
        "A_v_cache": _A_in["v_cache"],
        "A_wq": _A_in["wq"],
        "A_wo": _A_in["wo"],
        "B_x": _B_in["x"],
        "B_w1": _B_in["w1"],
        "B_b1": _B_in["b1"],
        "B_w2": _B_in["w2"],
        "gate_w": _w((lambda *s: torch.randn(*s, dtype=torch.bfloat16) * 0.05)(512) * 16.0),
    }

def reference(A_x, A_k_cache, A_v_cache, A_wq, A_wo, B_x, B_w1, B_b1, B_w2, gate_w):
    def _A_ref(x, k_cache, v_cache, wq, wo):
        B, Sq, D = x.shape
        Hq, Dh = 32, 128
        Hkv, Sk = k_cache.shape[1], k_cache.shape[2]
        W = min(4096, max(256, Sk // 4))
        rep = Hq // Hkv
        q = (lambda x, *d: x.permute(*d))((x @ wq).reshape(B, Sq, Hq, Dh), 0, 2, 1, 3)
        k = (lambda x, n, axis: torch.repeat_interleave(x, n, dim=axis))(k_cache[:, :, Sk - W:, :], rep, axis=1)
        v = (lambda x, n, axis: torch.repeat_interleave(x, n, dim=axis))(v_cache[:, :, Sk - W:, :], rep, axis=1)
        scores = torch.einsum("bhqd,bhkd->bhqk", q, k) * (Dh ** -0.5)
        p = _softmax(scores, axis=-1)
        o = torch.einsum("bhqk,bhkd->bhqd", p, v)
        return (lambda x, *d: x.permute(*d))(o, 0, 2, 1, 3).reshape(B, Sq, Hq * Dh) @ wo

    def _B_ref(x, w1, b1, w2):
        h = torch.einsum("bsd,df->bsf", x, w1) + b1
        sp = torch.log1p(torch.exp(-torch.abs(h))) + torch.where(h > 0, h, torch.zeros_like(h))
        act = h * torch.tanh(sp)
        return torch.einsum("bsf,fd->bsd", act, w2)

    x = A_x
    g = _sigmoid((x * gate_w).sum(-1, keepdims=True))
    a = _A_ref(x, A_k_cache, A_v_cache, A_wq, A_wo)
    b = _B_ref(x, B_w1, B_b1, B_w2)
    return g * a + (1 - g) * b
```

```cpp
#include <cuda_runtime.h>
#include <cuda_bf16.h>
#include <stdint.h>

namespace {

constexpr int NCTA     = 128;
constexpr int NCOMP    = 256;
constexpr int NLOAD    = 128;
constexpr int NTHREADS = NCOMP + NLOAD;
#define UNIT 4
#define WINDOW (32 / UNIT)
#define WSTAG 0
#define CSTAG 0
#define TAU_TAIL TAU_NS
#define TAU_NS 84
#define T_K 1600
#define INIT_SLOTS 1
#define BACKOFF_NS 64
#define O_EARLY 0
#define Q_LATE 1
#define E4_DELAY 0
#define BACKOFF_E4 0
#define BACKOFF_Q 200
constexpr int SPIN_LIMIT = 1 << 20;

constexpr int DM = 512, HQD = 4096, SK = 4096, WIN = 1024, FF = 1792;

constexpr int OFF_WQ   = 0;
constexpr int OFF_W1   = 32768;
constexpr int OFF_WO   = OFF_WQ;
constexpr int OFF_W2   = OFF_W1;
constexpr int OFF_K    = 49152;
constexpr int OFF_V    = OFF_K + 65536;
constexpr int OFF_XS   = OFF_V + 65536;
constexpr int OFF_PART = OFF_XS + 4 * 1040;
constexpr int OFF_QS   = OFF_PART + 6144;
constexpr int OFF_PS   = OFF_QS + 4 * 272;
constexpr int OFF_OS   = OFF_PS + 4 * 528;
constexpr int OFF_AS   = OFF_OS + 4 * 272;
constexpr int OFF_RED  = OFF_AS + 4 * 144;
constexpr int OFF_BAR  = OFF_RED + 320;
constexpr int SMEM_BYTES = OFF_BAR + 128;

enum { BAR_WQ = 0, BAR_K = 1, BAR_V0 = 2, BAR_W2 = 6, BAR_WO0 = 7, BAR_WO1 = 8, BAR_FREE = 9 };

constexpr int MB_QX = 0;
constexpr int MB_AX = MB_QX + 8 * 4 * 256;
constexpr int MB_LX = MB_AX + 112 * 32;
constexpr int MB_OX = MB_LX + NCTA * 16;
constexpr int MB_E4 = MB_OX + 32 * 16 * 64;
constexpr int MB_EP = MB_E4 + NCTA * 512;
constexpr int MB_WORDS = MB_EP + NCTA;
__device__ __align__(128) unsigned long long g_mail[MB_WORDS];
#define PROF_DECL
#define PROF_T(i) do {} while (0)
#define PROF_DUMP(base, n) do {} while (0)

__device__ __forceinline__ uint32_t smem_u32(const void* p) { return (uint32_t)__cvta_generic_to_shared(p); }
__device__ __forceinline__ void mbar_init(uint32_t bar, uint32_t cnt) {
    asm volatile("mbarrier.init.shared::cta.b64 [%0], %1;" ::"r"(bar), "r"(cnt) : "memory");
}
__device__ __forceinline__ void mbar_arrive(uint32_t bar) {
    asm volatile("mbarrier.arrive.shared::cta.b64 _, [%0];" ::"r"(bar) : "memory");
}
__device__ __forceinline__ void mbar_wait(uint32_t bar) {
    asm volatile("{\n.reg .pred p;\nW_%=:\nmbarrier.try_wait.parity.shared::cta.b64 p, [%0], 0;\n@!p bra W_%=;\n}" ::"r"(bar) : "memory");
}
__device__ __forceinline__ void cp_arrive(uint32_t bar) {
    asm volatile("cp.async.mbarrier.arrive.noinc.shared::cta.b64 [%0];" ::"r"(bar) : "memory");
}
__device__ __forceinline__ uint32_t gtime32() { uint32_t t; asm volatile("mov.u32 %0, %%globaltimer_lo;" : "=r"(t)); return t; }
__device__ __noinline__ int stream(uint32_t t0, int due, int tau, uint32_t dst, const char* src, uint32_t stride, int n) {
#pragma unroll 1
    for (int i = 0; i < n; i += UNIT) {
        if (tau > 0) {
            while ((int)(gtime32() - t0) < due) {}
            due += UNIT * tau;
        }
#pragma unroll
        for (int j = 0; j < UNIT; j++) {
            if (i + j < n) asm volatile("cp.async.cg.shared.global [%0], [%1], 16;" ::"r"(dst + j * 2048), "l"(src + (size_t)j * stride) : "memory");
        }
        asm volatile("cp.async.commit_group;\ncp.async.wait_group %0;" ::"n"(WINDOW - 1) : "memory");
        dst += UNIT * 2048;
        src += (size_t)UNIT * stride;
    }
    return due;
}
__device__ __forceinline__ void bar_comp() { asm volatile("bar.sync 1, 256;" ::: "memory"); }

__device__ __forceinline__ void ldsm4(uint32_t (&r)[4], uint32_t a) {
    asm volatile("ldmatrix.sync.aligned.m8n8.x4.shared.b16 {%0,%1,%2,%3}, [%4];"
                 : "=r"(r[0]), "=r"(r[1]), "=r"(r[2]), "=r"(r[3]) : "r"(a) : "memory");
}
__device__ __forceinline__ void ldsm4t(uint32_t (&r)[4], uint32_t a) {
    asm volatile("ldmatrix.sync.aligned.m8n8.x4.trans.shared.b16 {%0,%1,%2,%3}, [%4];"
                 : "=r"(r[0]), "=r"(r[1]), "=r"(r[2]), "=r"(r[3]) : "r"(a) : "memory");
}
__device__ __forceinline__ void mma16816(float (&c)[4], const uint32_t (&a)[4], uint32_t b0, uint32_t b1) {
    asm volatile("mma.sync.aligned.m16n8k16.row.col.f32.bf16.bf16.f32 {%0,%1,%2,%3}, {%4,%5,%6,%7}, {%8,%9}, {%0,%1,%2,%3};"
                 : "+f"(c[0]), "+f"(c[1]), "+f"(c[2]), "+f"(c[3])
                 : "r"(a[0]), "r"(a[1]), "r"(a[2]), "r"(a[3]), "r"(b0), "r"(b1));
}
__device__ __forceinline__ void mma1688(float (&c)[4], uint32_t a0, uint32_t a1, uint32_t b0) {
    asm volatile("mma.sync.aligned.m16n8k8.row.col.f32.bf16.bf16.f32 {%0,%1,%2,%3}, {%4,%5}, {%6}, {%0,%1,%2,%3};"
                 : "+f"(c[0]), "+f"(c[1]), "+f"(c[2]), "+f"(c[3])
                 : "r"(a0), "r"(a1), "r"(b0));
}
__device__ __forceinline__ void mma_tile64(float (&c0)[4], float (&c1)[4], uint32_t a, const uint32_t (&b0)[4], const uint32_t (&b1)[4]) {
    uint32_t f0[4], f1[4], f2[4], f3[4];
    ldsm4t(f0, a);
    ldsm4t(f1, a + 16 * 256);
    ldsm4t(f2, a + 32 * 256);
    ldsm4t(f3, a + 48 * 256);
    mma16816(c0, f0, b0[0], b0[1]);
    mma16816(c1, f1, b0[2], b0[3]);
    mma16816(c0, f2, b1[0], b1[1]);
    mma16816(c1, f3, b1[2], b1[3]);
}
__device__ __forceinline__ uint32_t pack_bf16(float lo, float hi) {
    uint32_t r;
    asm("cvt.rn.bf16x2.f32 %0, %1, %2;" : "=r"(r) : "f"(hi), "f"(lo));
    return r;
}
__device__ __forceinline__ float bf_lo(uint32_t v) { return __uint_as_float(v << 16); }
__device__ __forceinline__ float bf_hi(uint32_t v) { return __uint_as_float(v & 0xffff0000u); }
__device__ __forceinline__ float ex2(float x) { float y; asm("ex2.approx.ftz.f32 %0, %1;" : "=f"(y) : "f"(x)); return y; }
__device__ __forceinline__ float lg2(float x) { float y; asm("lg2.approx.ftz.f32 %0, %1;" : "=f"(y) : "f"(x)); return y; }
__device__ __forceinline__ float rcp(float x) { float y; asm("rcp.approx.ftz.f32 %0, %1;" : "=f"(y) : "f"(x)); return y; }
__device__ __forceinline__ float dot2(uint32_t a, uint32_t b, float acc) {
    return fmaf(bf_hi(a), bf_hi(b), fmaf(bf_lo(a), bf_lo(b), acc));
}
__device__ __forceinline__ void sts32(uint32_t a, uint32_t v) { asm volatile("st.shared.b32 [%0], %1;" ::"r"(a), "r"(v) : "memory"); }
__device__ __forceinline__ void sts16(uint32_t a, uint32_t v) { asm volatile("st.shared.b16 [%0], %1;" ::"r"(a), "h"((unsigned short)v) : "memory"); }

__device__ __forceinline__ void ll_store(unsigned long long* p, uint32_t payload, uint32_t epoch) {
    asm volatile("{\n.reg .b64 v;\nmov.b64 v, {%1, %2};\nst.relaxed.gpu.global.b64 [%0], v;\n}" ::"l"(p), "r"(payload), "r"(epoch) : "memory");
}
__device__ __forceinline__ uint2 ll_load(const unsigned long long* p) {
    uint2 v;
    asm volatile("{\n.reg .b64 v;\nld.relaxed.gpu.global.b64 v, [%2];\nmov.b64 {%0, %1}, v;\n}" : "=r"(v.x), "=r"(v.y) : "l"(p) : "memory");
    return v;
}
template <int N, int STRIDE, int SLEEP>
__device__ __forceinline__ void ll_finish(uint2 (&v)[N], const unsigned long long* p, uint32_t epoch) {
#pragma unroll 1
    for (int it = 0; it < SPIN_LIMIT; it++) {
        bool ok = true;
#pragma unroll
        for (int i = 0; i < N; i++) ok = ok && v[i].y == epoch;
        if (ok) break;
        if (SLEEP) __nanosleep(SLEEP);
#pragma unroll
        for (int i = 0; i < N; i++)
            if (v[i].y != epoch) v[i] = ll_load(p + i * STRIDE);
    }
}

constexpr float LOG2E = 1.4426950408889634f;
__device__ __forceinline__ float mish(float h) {
    const float e = ex2(-fabsf(h) * LOG2E);
    const float num = h >= 0.f ? fmaf(2.f, e, 1.f) : e * (e + 2.f);
    const float den = num + (h >= 0.f ? 2.f * e * e : 2.f);
    return h * num * rcp(den);
}

__global__ void __launch_bounds__(NTHREADS, 1)
fused_decode_kernel(const __nv_bfloat16* __restrict__ x, const __nv_bfloat16* __restrict__ kc,
                    const __nv_bfloat16* __restrict__ vc, const __nv_bfloat16* __restrict__ wq,
                    const __nv_bfloat16* __restrict__ wo, const __nv_bfloat16* __restrict__ w1,
                    const __nv_bfloat16* __restrict__ b1, const __nv_bfloat16* __restrict__ w2,
                    const __nv_bfloat16* __restrict__ gw, __nv_bfloat16* __restrict__ out) {
    extern __shared__ __align__(128) unsigned char smem[];
    const uint32_t sb = smem_u32(smem);
    const int tid = threadIdx.x;
    const int cta = blockIdx.x;
    const int kvh = cta >> 4, r = cta & 15;
    const int hj = cta >> 2, cq = cta & 3;
    const uint32_t bar0 = sb + OFF_BAR;

    if (tid >= NCOMP) {
        const int lt = tid - NCOMP;
        PROF_DECL;
        PROF_T(16);
        const uint32_t t0 = gtime32();
        {
            const int row = lt >> 2, c = lt & 3;
            const char* src = (const char*)wq + (size_t)row * (HQD * 2) + cta * 64 + c * 16;
            const uint32_t dst = sb + OFF_WQ + row * 64 + ((c ^ ((row >> 1) & 3)) << 4);
            stream(0, 0, 0, dst, src, 32 * HQD * 2, 16);
        }
        {
            const int row = lt >> 1, c = lt & 1;
            stream(0, 0, 0, sb + OFF_W1 + row * 32 + ((c ^ ((row >> 2) & 1)) << 4),
                   (const char*)w1 + (size_t)row * (FF * 2) + cta * 32 + c * 16, 64 * FF * 2, cta < 112 ? 8 : 0);
        }
        if (lt <= BAR_FREE) mbar_init(bar0 + 8 * lt, lt == BAR_FREE ? 8 : NLOAD);
        asm volatile("bar.sync 2, 128;\nbar.arrive 0, 384;" ::: "memory");
        cp_arrive(bar0 + 8 * BAR_WQ);
        const int row = lt >> 4, c = lt & 15;
        const uint32_t sw = sb + row * 256 + ((c ^ row) << 4);
        const size_t kvoff = ((size_t)((r >> 2) * 8 + kvh) * SK + (SK - WIN) + (r & 3) * 256) * 256 + lt * 16;
        int due = stream(t0, T_K + (lt >> 5) * WSTAG + r * CSTAG, TAU_NS, sw + OFF_K, (const char*)kc + kvoff, 2048, 32);
        cp_arrive(bar0 + 8 * BAR_K);
        PROF_T(17);
#pragma unroll 1
        for (int ch = 0; ch < 4; ch++) {
            due = stream(t0, due, TAU_NS, sw + OFF_V + ch * 16384, (const char*)vc + kvoff + ch * 16384, 2048, 8);
            cp_arrive(bar0 + 8 * (BAR_V0 + ch));
        }
        PROF_T(18);
        mbar_wait(bar0 + 8 * BAR_FREE);
        const int wofs = row * (DM * 2) + cq * 256 + c * 16;
        due = stream(t0, due, TAU_TAIL, sw + OFF_W2, (const char*)w2 + hj * (56 * DM * 2) + wofs, 8 * DM * 2, 7);
        cp_arrive(bar0 + 8 * BAR_W2);
#pragma unroll 1
        for (int ch = 0; ch < 2; ch++) {
            due = stream(t0, due, TAU_TAIL, sw + OFF_WO + ch * 16384, (const char*)wo + (hj * 2 + ch) * (64 * DM * 2) + wofs, 8 * DM * 2, 8);
            cp_arrive(bar0 + 8 * (BAR_WO0 + ch));
        }
        PROF_T(19);
        asm volatile("cp.async.wait_all;" ::: "memory");
        PROF_T(20);
        if (lt == 0) PROF_DUMP(16, 5);
        return;
    }

    const int lane = tid & 31, w = tid >> 5;
    const int g = lane >> 2, t = lane & 3;
    const int t1 = t & 1, th = t >> 1;
    const int mi = lane >> 3, l8 = lane & 7;
    const int ab = r >> 2;
    PROF_DECL;
    PROF_T(0);
    float* const part = reinterpret_cast<float*>(smem + OFF_PART);
    float* const wmax = reinterpret_cast<float*>(smem + OFF_RED);
    float* const wsum = wmax + 32;
    float* const gpart = wmax + 64;
    unsigned long long* const mail = g_mail;

    const uint4 xv = __ldg(reinterpret_cast<const uint4*>(x) + tid);
    const uint4 gv = __ldg(reinterpret_cast<const uint4*>(gw) + (tid & 63));
    const uint32_t epoch = *(volatile unsigned int*)&mail[MB_EP + cta] + 1u;
    const uint32_t b1v = __ldg(reinterpret_cast<const uint32_t*>(b1 + (cta < 112 ? cta : 0) * 16) + (tid & 7));
    const int hb = 2 * t1 + th;
    unsigned long long* const ox_slot = mail + MB_OX + ((kvh * 4 + hb) * 16 + r) * 64 + w * 8 + g;
    unsigned long long* const e4_slot = mail + MB_E4 + (((hb * 8 + w) * 4 + cq) * 32 + hj) * 16 + g;
    ll_store(ox_slot, 0u, 0u);
    if (tid < 64) ll_store(mail + MB_QX + (kvh * 4 + (tid >> 4)) * 256 + r * 16 + (tid & 15), 0u, 0u);
    if (tid < 16 && t == cq) ll_store(mail + MB_LX + cta * 16 + g, 0u, 0u);
    ll_store(e4_slot, 0u, 0u);
    ll_store(e4_slot + 8, 0u, 0u);
    *reinterpret_cast<uint4*>(smem + OFF_XS + (tid >> 6) * 1040 + (tid & 63) * 16) = xv;
    {
        float acc = dot2(xv.w, gv.w, dot2(xv.z, gv.z, dot2(xv.y, gv.y, dot2(xv.x, gv.x, 0.f))));
#pragma unroll
        for (int o = 16; o > 0; o >>= 1) acc += __shfl_xor_sync(0xffffffffu, acc, o);
        if (lane == 0) gpart[w] = acc;
    }
    asm volatile("bar.sync 0, 384;" ::: "memory");
    PROF_T(1);

    {
        uint32_t xb[2][4];
        const uint32_t xa = sb + OFF_XS + (l8 & 3) * 1040 + (w * 64 + mi * 8) * 2;
        ldsm4(xb[0], xa);
        ldsm4(xb[1], xa + 64);
        const int kr = w * 64 + l8 + ((mi >> 1) << 3);
        const uint32_t aq0 = sb + OFF_WQ + kr * 64 + (((mi & 1) ^ ((kr >> 1) & 3)) << 4);
        const uint32_t aq1 = aq0 ^ 32;
        const uint32_t ah = sb + OFF_W1 + kr * 32 + (((mi & 1) ^ ((kr >> 2) & 1)) << 4);
        float cq0[4] = {0.f, 0.f, 0.f, 0.f}, cq1[4] = {0.f, 0.f, 0.f, 0.f}, ch[4] = {0.f, 0.f, 0.f, 0.f};
        mbar_wait(bar0 + 8 * BAR_WQ);
        PROF_T(2);
#pragma unroll
        for (int ks = 0; ks < 4; ks++) {
            uint32_t a0[4], a1[4], a2[4];
            ldsm4t(a0, aq0 + ks * 1024);
            ldsm4t(a1, aq1 + ks * 1024);
            ldsm4t(a2, ah + ks * 512);
            const uint32_t bb0 = xb[ks >> 1][(ks & 1) * 2], bb1 = xb[ks >> 1][(ks & 1) * 2 + 1];
            mma16816(cq0, a0, bb0, bb1);
            mma16816(cq1, a1, bb0, bb1);
            mma16816(ch, a2, bb0, bb1);
        }
        __syncwarp();
        if (lane == 0) mbar_arrive(bar0 + 8 * BAR_FREE);
        if (t < 2) {
            float* p0 = part + (w * 4 + 2 * t) * 48 + g;
            p0[0] = cq0[0]; p0[48] = cq0[1]; p0[8] = cq0[2]; p0[56] = cq0[3];
            p0[16] = cq1[0]; p0[64] = cq1[1]; p0[24] = cq1[2]; p0[72] = cq1[3];
            p0[32] = ch[0]; p0[80] = ch[1]; p0[40] = ch[2]; p0[88] = ch[3];
        }
        bar_comp();
        if (tid < 96) {
            const bool isq = tid < 64;
            const int b = isq ? tid >> 4 : (tid - 64) >> 3;
            const int cp = isq ? tid & 15 : 16 + (tid & 7);
            float v0 = 0.f, v1 = 0.f;
#pragma unroll
            for (int i = 0; i < 8; i++) {
                const float2 v = *reinterpret_cast<const float2*>(part + (i * 4 + b) * 48 + 2 * cp);
                v0 += v.x; v1 += v.y;
            }
            if (!isq) { v0 = mish(v0 + bf_lo(b1v)); v1 = mish(v1 + bf_hi(b1v)); }
            const int slot = isq ? MB_QX + (kvh * 4 + b) * 256 + r * 16 + cp : MB_AX + cta * 32 + (tid - 64);
            if (isq || cta < 112) ll_store(mail + slot, pack_bf16(v0, v1), epoch);
        }
    }
    PROF_T(3);

    mbar_wait(bar0 + 8 * BAR_K);
    {
        const unsigned long long* qp = mail + MB_QX + (kvh * 4 + ab) * 256 + tid;
        uint2 v[1] = {ll_load(qp)};
        ll_finish<1, 1, BACKOFF_Q>(v, qp, epoch);
        sts32(sb + OFF_QS + (tid >> 6) * 272 + (tid & 63) * 4, v[0].x);
    }
    bar_comp();
    PROF_T(5);

    constexpr float SC = 0.08838834764831845f * LOG2E;
    {
        float s0[4] = {0.f, 0.f, 0.f, 0.f}, s1[4] = {0.f, 0.f, 0.f, 0.f};
        const uint32_t qa = sb + OFF_QS + (l8 & 3) * 272 + mi * 16;
        const uint32_t kb = sb + OFF_K + (w * 32 + (lane & 15)) * 256;
        const int kx = (lane >> 4) ^ l8;
        mbar_wait(bar0 + 8 * BAR_K);
        PROF_T(4);
#pragma unroll
        for (int i = 0; i < 4; i++) {
            uint32_t qb[4], a0[4], a1[4], a2[4], a3[4];
            const uint32_t o0 = (uint32_t)((kx ^ (4 * i)) << 4), o1 = o0 ^ 32;
            ldsm4(qb, qa + i * 64);
            ldsm4(a0, kb + o0);
            ldsm4(a1, kb + 16 * 256 + o0);
            ldsm4(a2, kb + o1);
            ldsm4(a3, kb + 16 * 256 + o1);
            mma16816(s0, a0, qb[0], qb[1]);
            mma16816(s1, a1, qb[0], qb[1]);
            mma16816(s0, a2, qb[2], qb[3]);
            mma16816(s1, a3, qb[2], qb[3]);
        }
        float m0 = fmaxf(fmaxf(s0[0], s0[2]), fmaxf(s1[0], s1[2]));
        float m1 = fmaxf(fmaxf(s0[1], s0[3]), fmaxf(s1[1], s1[3]));
#pragma unroll
        for (int o = 4; o < 32; o <<= 1) {
            m0 = fmaxf(m0, __shfl_xor_sync(0xffffffffu, m0, o));
            m1 = fmaxf(m1, __shfl_xor_sync(0xffffffffu, m1, o));
        }
        if (lane < 2) *reinterpret_cast<float2*>(wmax + w * 4 + 2 * lane) = make_float2(m0, m1);
        bar_comp();
#pragma unroll
        for (int i = 0; i < 8; i++) {
            const float2 v = *reinterpret_cast<const float2*>(wmax + i * 4 + 2 * t1);
            m0 = fmaxf(m0, v.x); m1 = fmaxf(m1, v.y);
        }
        const float n0 = m0 * SC, n1 = m1 * SC;
        const uint32_t pa = pack_bf16(ex2(fmaf(th ? s1[0] : s0[0], SC, -n0)), ex2(fmaf(th ? s1[2] : s0[2], SC, -n0)));
        const uint32_t pb = pack_bf16(ex2(fmaf(th ? s1[1] : s0[1], SC, -n1)), ex2(fmaf(th ? s1[3] : s0[3], SC, -n1)));
        const uint32_t pd = sb + OFF_PS + t1 * (2 * 528) + (w * 32 + th * 16 + g) * 2;
        sts16(pd, pa); sts16(pd + 16, pa >> 16); sts16(pd + 528, pb); sts16(pd + 544, pb >> 16);
        float l0 = bf_lo(pa) + bf_hi(pa), l1 = bf_lo(pb) + bf_hi(pb);
#pragma unroll
        for (int o = 2; o < 32; o <<= 1) {
            l0 += __shfl_xor_sync(0xffffffffu, l0, o);
            l1 += __shfl_xor_sync(0xffffffffu, l1, o);
        }
        if (lane < 2) *reinterpret_cast<float2*>(wsum + w * 4 + 2 * lane) = make_float2(l0, l1);
        bar_comp();
    }
    PROF_T(6);

    const uint32_t a_off = (l8 + ((mi >> 1) << 3)) * 256 + (((2 * w + (mi & 1)) ^ l8) << 4);
    {
        const int hd = (lane >> 2) & 3;
        float l = 0.f, m = wmax[hd];
#pragma unroll
        for (int i = 0; i < 8; i++) { l += wsum[i * 4 + hd]; m = fmaxf(m, wmax[i * 4 + hd]); }
        m *= SC;
        const unsigned long long* lp = mail + MB_LX + ((cta & ~3) + t) * 16 + hd;
        if (tid < 16 && t == cq) ll_store(const_cast<unsigned long long*>(lp), __float_as_uint(m + lg2(l)), epoch);
        if (tid >= 128 && tid < 240) {
            const int b = (tid - 128) / 28, e = tid - 128 - b * 28, ge = hj * 28 + e;
            const unsigned long long* ap = mail + MB_AX + (ge >> 3) * 32 + b * 8 + (ge & 7);
            uint2 av[1] = {ll_load(ap)};
            ll_finish<1, 1, BACKOFF_NS>(av, ap, epoch);
            sts32(sb + OFF_AS + b * 144 + e * 4, av[0].x);
        }
        float o0[4] = {0.f, 0.f, 0.f, 0.f}, o1[4] = {0.f, 0.f, 0.f, 0.f};
        const uint32_t pb = sb + OFF_PS + (l8 & 3) * 528 + mi * 16;
        uint2 lv[1];
        float wgt;
#pragma unroll 1
        for (int ch = 0; ch < 4; ch++) {
            uint32_t pf0[4], pf1[4];
            ldsm4(pf0, pb + ch * 128);
            ldsm4(pf1, pb + ch * 128 + 64);
            if (ch == 2) lv[0] = ll_load(lp);
            if (ch == 3) {
                ll_finish<1, 1, BACKOFF_NS>(lv, lp, epoch);
                const float e = __uint_as_float(lv[0].x);
                float mx = fmaxf(e, __shfl_xor_sync(0xffffffffu, e, 1));
                mx = fmaxf(mx, __shfl_xor_sync(0xffffffffu, mx, 2));
                float den = ex2(e - mx);
                den += __shfl_xor_sync(0xffffffffu, den, 1);
                den += __shfl_xor_sync(0xffffffffu, den, 2);
                wgt = __shfl_sync(0xffffffffu, ex2(m - mx) * rcp(den), hb * 4);
            }
            mbar_wait(bar0 + 8 * (BAR_V0 + ch));
            PROF_T(14);
            mma_tile64(o0, o1, sb + OFF_V + ch * 16384 + a_off, pf0, pf1);
        }
        PROF_T(7);
        const float va = (th ? o0[1] + o1[1] : o0[0] + o1[0]) * wgt;
        const float vb = (th ? o0[3] + o1[3] : o0[2] + o1[2]) * wgt;
        ll_store(ox_slot, pack_bf16(va, vb), epoch);
    }
    PROF_T(8);

    {
        const unsigned long long* op = mail + MB_OX + (hj * 16 + (tid >> 6) * 4) * 64 + (tid & 63);
        uint2 ov[4];
        bar_comp();
        float bq[4] = {0.f, 0.f, 0.f, 0.f}, b2[4] = {0.f, 0.f, 0.f, 0.f};
        {
            uint32_t af0[4], af1[4], f0[4], f1[4], f2[4], f3[4];
            const uint32_t aa = sb + OFF_AS + (l8 & 3) * 144 + mi * 16;
            ldsm4(af0, aa);
            ldsm4(af1, aa + 64);
            mbar_wait(bar0 + 8 * BAR_W2);
            const uint32_t wb = sb + OFF_W2 + a_off;
            ldsm4t(f0, wb);
            ldsm4t(f1, wb + 16 * 256);
            ldsm4t(f2, wb + 32 * 256);
            ldsm4t(f3, wb + 48 * 256);
            mma16816(bq, f0, af0[0], af0[1]);
            mma16816(b2, f1, af0[2], af0[3]);
            mma16816(bq, f2, af1[0], af1[1]);
            mma1688(b2, f3[0], f3[1], af1[2]);
        }
        const float gt = rcp(1.f + ex2(-(gpart[2 * hb] + gpart[2 * hb + 1]) * LOG2E));
        const float rb = (1.f - gt) * (th ? bq[1] + b2[1] : bq[0] + b2[0]);
        const float rd = (1.f - gt) * (th ? bq[3] + b2[3] : bq[2] + b2[2]);
        PROF_T(11);
#pragma unroll
        for (int s = 0; s < 4; s++) ov[s] = ll_load(op + s * 64);
        ll_finish<4, 64, BACKOFF_NS>(ov, op, epoch);
        {
            const float v0 = (bf_lo(ov[0].x) + bf_lo(ov[1].x)) + (bf_lo(ov[2].x) + bf_lo(ov[3].x));
            const float v1 = (bf_hi(ov[0].x) + bf_hi(ov[1].x)) + (bf_hi(ov[2].x) + bf_hi(ov[3].x));
            const uint32_t pk = pack_bf16(v0, v1);
            const uint32_t od = sb + OFF_OS + (tid >> 6) * 272 + (tid & 56) * 4 + (tid & 7) * 2;
            sts16(od, pk); sts16(od + 16, pk >> 16);
        }
        bar_comp();
        PROF_T(9);
        uint32_t of[4][4];
        const uint32_t fb = sb + OFF_OS + (l8 & 3) * 272 + mi * 16;
#pragma unroll
        for (int i = 0; i < 4; i++) ldsm4(of[i], fb + i * 64);
        float a0[4] = {0.f, 0.f, 0.f, 0.f}, a1[4] = {0.f, 0.f, 0.f, 0.f};
        mbar_wait(bar0 + 8 * BAR_WO0);
        mma_tile64(a0, a1, sb + OFF_WO + a_off, of[0], of[1]);
        mbar_wait(bar0 + 8 * BAR_WO1);
        PROF_T(10);
        mma_tile64(a0, a1, sb + OFF_WO + 16384 + a_off, of[2], of[3]);
        ll_store(e4_slot,     __float_as_uint(fmaf(gt, th ? a0[1] + a1[1] : a0[0] + a1[0], rb)), epoch);
        ll_store(e4_slot + 8, __float_as_uint(fmaf(gt, th ? a0[3] + a1[3] : a0[2] + a1[2], rd)), epoch);
    }
    PROF_T(12);

    {
        const unsigned long long* ep = mail + MB_E4 + cta * 512 + w * 64 + lane;
        if (E4_DELAY) __nanosleep(E4_DELAY);
        uint2 v[2] = {ll_load(ep), ll_load(ep + 32)};
        ll_finish<2, 32, BACKOFF_E4>(v, ep, epoch);
        PROF_T(15);
        float acc = __uint_as_float(v[0].x) + __uint_as_float(v[1].x);
        acc += __shfl_xor_sync(0xffffffffu, acc, 16);
        if (lane < 16) part[w * 16 + lane] = acc;
        bar_comp();
        if (tid < 16) {
            float s0 = 0.f, s1 = 0.f;
#pragma unroll
            for (int i = 0; i < 4; i++) { s0 += part[i * 32 + tid]; s1 += part[i * 32 + 16 + tid]; }
            out[(hj >> 3) * DM + cq * 128 + (hj & 7) * 16 + tid] = __float2bfloat16(s0 + s1);
            if (tid == 0) *(volatile unsigned int*)&mail[MB_EP + cta] = epoch;
        }
        PROF_T(13);
        if (tid == 0) PROF_DUMP(0, 16);
    }
}

}

extern "C" void kernel_launch(void* const* d_in, const int* in_sizes, int n_in, void* d_out, int out_size) {
    (void)in_sizes; (void)n_in; (void)out_size;
    const __nv_bfloat16* x  = (const __nv_bfloat16*)d_in[0];
    const __nv_bfloat16* kc = (const __nv_bfloat16*)d_in[1];
    const __nv_bfloat16* vc = (const __nv_bfloat16*)d_in[2];
    const __nv_bfloat16* wq = (const __nv_bfloat16*)d_in[3];
    const __nv_bfloat16* wo = (const __nv_bfloat16*)d_in[4];
    const __nv_bfloat16* w1 = (const __nv_bfloat16*)d_in[6];
    const __nv_bfloat16* b1 = (const __nv_bfloat16*)d_in[7];
    const __nv_bfloat16* w2 = (const __nv_bfloat16*)d_in[8];
    const __nv_bfloat16* gw = (const __nv_bfloat16*)d_in[9];
    cudaFuncSetAttribute(fused_decode_kernel, cudaFuncAttributeMaxDynamicSharedMemorySize, SMEM_BYTES);
    fused_decode_kernel<<<NCTA, NTHREADS, SMEM_BYTES, cudaStreamPerThread>>>(x, kc, vc, wq, wo, w1, b1, w2, gw,
                                                                            (__nv_bfloat16*)d_out);
}
```

```cpp
#include <cuda_runtime.h>
#include <cuda_bf16.h>
#include <stdint.h>

namespace {

constexpr int NCTA     = 128;
constexpr int NCOMP    = 256;
constexpr int NLOAD    = 128;
constexpr int NTHREADS = NCOMP + NLOAD;
#define WINDOW 8
#define TAU_TAIL TAU_NS
#define TAU_NS 84
#define T_K 1100
#define INIT_SLOTS 1
#define BACKOFF_NS 64
#define EVICT_FIRST 1
#define O_EARLY 0
#define Q_LATE 1
#define NPOLL 3
#define POLL_GAP 60
#define BACKOFF_E4 0
#define BACKOFF_Q 200
constexpr int SPIN_LIMIT = 1 << 20;

constexpr int DM = 512, HQD = 4096, SK = 4096, WIN = 1024, FF = 1792;

constexpr int OFF_WQ   = 0;
constexpr int OFF_W1   = 32768;
constexpr int OFF_WO   = OFF_WQ;
constexpr int OFF_W2   = OFF_W1;
constexpr int OFF_K    = 49152;
constexpr int OFF_V    = OFF_K + 65536;
constexpr int OFF_XS   = OFF_V + 65536;
constexpr int OFF_PART = OFF_XS + 4 * 1040;
constexpr int OFF_QS   = OFF_PART + 6144;
constexpr int OFF_PS   = OFF_QS + 4 * 272;
constexpr int OFF_OS   = OFF_PS + 4 * 528;
constexpr int OFF_AS   = OFF_OS + 4 * 272;
constexpr int OFF_RED  = OFF_AS + 4 * 144;
constexpr int OFF_BAR  = OFF_RED + 320;
constexpr int SMEM_BYTES = OFF_BAR + 128;

enum { BAR_WQ = 0, BAR_K = 1, BAR_V0 = 2, BAR_W2 = 6, BAR_WO0 = 7, BAR_WO1 = 8, BAR_WO2 = 9, BAR_FREE = 10 };

constexpr int MB_QX = 0;
constexpr int MB_AX = MB_QX + 8 * 4 * 256;
constexpr int MB_LX = MB_AX + 112 * 32;
constexpr int MB_OX = MB_LX + NCTA * 16;
constexpr int MB_E4 = MB_OX + 32 * 16 * 64;
constexpr int MB_EP = MB_E4 + NCTA * 512;
constexpr int MB_WORDS = MB_EP + NCTA;
#define MAIL_PAD_WORDS 0
#define MAIL_OFF_WORDS 0
__device__ __align__(128) unsigned long long g_mail[MB_WORDS + MAIL_PAD_WORDS];
#define PROF_DECL
#define PROF_T(i) do {} while (0)
#define PROF_DUMP(base, n) do {} while (0)

__device__ __forceinline__ uint32_t smem_u32(const void* p) { return (uint32_t)__cvta_generic_to_shared(p); }
__device__ __forceinline__ void mbar_init(uint32_t bar, uint32_t cnt) {
    asm volatile("mbarrier.init.shared::cta.b64 [%0], %1;" ::"r"(bar), "r"(cnt) : "memory");
}
__device__ __forceinline__ void mbar_arrive(uint32_t bar) {
    asm volatile("mbarrier.arrive.shared::cta.b64 _, [%0];" ::"r"(bar) : "memory");
}
__device__ __forceinline__ void mbar_wait(uint32_t bar) {
    asm volatile("{\n.reg .pred p;\nW_%=:\nmbarrier.try_wait.parity.shared::cta.b64 p, [%0], 0;\n@!p bra W_%=;\n}" ::"r"(bar) : "memory");
}
__device__ __forceinline__ void cp_arrive(uint32_t bar) {
    asm volatile("cp.async.mbarrier.arrive.noinc.shared::cta.b64 [%0];" ::"r"(bar) : "memory");
}
template <int N, int SSTRIDE, int J = 0>
__device__ __forceinline__ void cp_steps(uint32_t dst, const char* src) {
    if constexpr (J < N) {
        asm volatile("{\n.reg .b64 pol;\ncreatepolicy.fractional.L2::evict_first.b64 pol, 1.0;\n"
                     "cp.async.cg.shared.global.L2::cache_hint [%0 + %2], [%1 + %3], 16, pol;\n}"
                     ::"r"(dst), "l"(src), "n"(J * 2048), "n"(J * SSTRIDE) : "memory");
        cp_steps<N, SSTRIDE, J + 1>(dst, src);
    }
}
template <int UNITS, int SSTRIDE>
__device__ __forceinline__ void burst(uint32_t dst, const char* src) {
#pragma unroll 1
    for (int i = 0; i < UNITS; i++) {
        cp_steps<4, SSTRIDE>(dst, src);
        dst += 4 * 2048;
        src += 4 * SSTRIDE;
    }
}
__device__ __forceinline__ uint32_t gtime32() { uint32_t t; asm volatile("mov.u32 %0, %%globaltimer_lo;" : "=r"(t)); return t; }
template <int N, int SSTRIDE, int TAU>
__device__ __forceinline__ void paced_unit(uint32_t t0, int& due, uint32_t dst, const char* src) {
    if (TAU > 0) {
        while ((int)(gtime32() - t0) < due) {}
        due += N * TAU;
    }
    cp_steps<N, SSTRIDE>(dst, src);
    asm volatile("cp.async.commit_group;\ncp.async.wait_group %0;" ::"n"(WINDOW - 1) : "memory");
}
template <int UNITS, int SSTRIDE, int TAU>
__device__ __forceinline__ void stream(uint32_t t0, int& due, uint32_t dst, const char* src) {
#pragma unroll 1
    for (int i = 0; i < UNITS; i++) {
        paced_unit<4, SSTRIDE, TAU>(t0, due, dst, src);
        dst += 4 * 2048;
        src += 4 * SSTRIDE;
    }
}
__device__ __forceinline__ void bar_comp() { asm volatile("bar.sync 1, 256;" ::: "memory"); }

__device__ __forceinline__ void ldsm4(uint32_t (&r)[4], uint32_t a) {
    asm volatile("ldmatrix.sync.aligned.m8n8.x4.shared.b16 {%0,%1,%2,%3}, [%4];"
                 : "=r"(r[0]), "=r"(r[1]), "=r"(r[2]), "=r"(r[3]) : "r"(a) : "memory");
}
__device__ __forceinline__ void ldsm4t(uint32_t (&r)[4], uint32_t a) {
    asm volatile("ldmatrix.sync.aligned.m8n8.x4.trans.shared.b16 {%0,%1,%2,%3}, [%4];"
                 : "=r"(r[0]), "=r"(r[1]), "=r"(r[2]), "=r"(r[3]) : "r"(a) : "memory");
}
__device__ __forceinline__ void mma16816(float (&c)[4], const uint32_t (&a)[4], uint32_t b0, uint32_t b1) {
    asm volatile("mma.sync.aligned.m16n8k16.row.col.f32.bf16.bf16.f32 {%0,%1,%2,%3}, {%4,%5,%6,%7}, {%8,%9}, {%0,%1,%2,%3};"
                 : "+f"(c[0]), "+f"(c[1]), "+f"(c[2]), "+f"(c[3])
                 : "r"(a[0]), "r"(a[1]), "r"(a[2]), "r"(a[3]), "r"(b0), "r"(b1));
}
__device__ __forceinline__ void mma1688(float (&c)[4], uint32_t a0, uint32_t a1, uint32_t b0) {
    asm volatile("mma.sync.aligned.m16n8k8.row.col.f32.bf16.bf16.f32 {%0,%1,%2,%3}, {%4,%5}, {%6}, {%0,%1,%2,%3};"
                 : "+f"(c[0]), "+f"(c[1]), "+f"(c[2]), "+f"(c[3])
                 : "r"(a0), "r"(a1), "r"(b0));
}
__device__ __forceinline__ void mma_tile64(float (&c0)[4], float (&c1)[4], uint32_t a, const uint32_t (&b0)[4], const uint32_t (&b1)[4]) {
    uint32_t f0[4], f1[4], f2[4], f3[4];
    ldsm4t(f0, a);
    ldsm4t(f1, a + 16 * 256);
    ldsm4t(f2, a + 32 * 256);
    ldsm4t(f3, a + 48 * 256);
    mma16816(c0, f0, b0[0], b0[1]);
    mma16816(c1, f1, b0[2], b0[3]);
    mma16816(c0, f2, b1[0], b1[1]);
    mma16816(c1, f3, b1[2], b1[3]);
}
__device__ __forceinline__ uint32_t pack_bf16(float lo, float hi) {
    uint32_t r;
    asm("cvt.rn.bf16x2.f32 %0, %1, %2;" : "=r"(r) : "f"(hi), "f"(lo));
    return r;
}
__device__ __forceinline__ float bf_lo(uint32_t v) { return __uint_as_float(v << 16); }
__device__ __forceinline__ float bf_hi(uint32_t v) { return __uint_as_float(v & 0xffff0000u); }
__device__ __forceinline__ float ex2(float x) { float y; asm("ex2.approx.ftz.f32 %0, %1;" : "=f"(y) : "f"(x)); return y; }
__device__ __forceinline__ float lg2(float x) { float y; asm("lg2.approx.ftz.f32 %0, %1;" : "=f"(y) : "f"(x)); return y; }
__device__ __forceinline__ float rcp(float x) { float y; asm("rcp.approx.ftz.f32 %0, %1;" : "=f"(y) : "f"(x)); return y; }
__device__ __forceinline__ float dot2(uint32_t a, uint32_t b, float acc) {
    return fmaf(bf_hi(a), bf_hi(b), fmaf(bf_lo(a), bf_lo(b), acc));
}
__device__ __forceinline__ void sts32(uint32_t a, uint32_t v) { asm volatile("st.shared.b32 [%0], %1;" ::"r"(a), "r"(v) : "memory"); }
__device__ __forceinline__ void sts16(uint32_t a, uint32_t v) { asm volatile("st.shared.b16 [%0], %1;" ::"r"(a), "h"((unsigned short)v) : "memory"); }

__device__ __forceinline__ void ll_store(unsigned long long* p, uint32_t payload, uint32_t epoch) {
    asm volatile("{\n.reg .b64 v;\nmov.b64 v, {%1, %2};\nst.relaxed.gpu.global.b64 [%0], v;\n}" ::"l"(p), "r"(payload), "r"(epoch) : "memory");
}
__device__ __forceinline__ uint2 ll_load(const unsigned long long* p) {
    uint2 v;
    asm volatile("{\n.reg .b64 v;\nld.relaxed.gpu.global.b64 v, [%2];\nmov.b64 {%0, %1}, v;\n}" : "=r"(v.x), "=r"(v.y) : "l"(p) : "memory");
    return v;
}
template <int N, int STRIDE, int SLEEP>
__device__ __forceinline__ void ll_finish(uint2 (&v)[N], const unsigned long long* p, uint32_t epoch) {
#pragma unroll 1
    for (int it = 0; it < SPIN_LIMIT; it++) {
        bool ok = true;
#pragma unroll
        for (int i = 0; i < N; i++) ok = ok && v[i].y == epoch;
        if (ok) break;
        if (SLEEP) __nanosleep(SLEEP);
#pragma unroll
        for (int i = 0; i < N; i++)
            if (v[i].y != epoch) v[i] = ll_load(p + i * STRIDE);
    }
}

constexpr float LOG2E = 1.4426950408889634f;
__device__ __forceinline__ float mish(float h) {
    const float e = ex2(-fabsf(h) * LOG2E);
    const float num = h >= 0.f ? fmaf(2.f, e, 1.f) : e * (e + 2.f);
    const float den = num + (h >= 0.f ? 2.f * e * e : 2.f);
    return h * num * rcp(den);
}

__global__ void __launch_bounds__(NTHREADS, 1)
fused_decode_kernel(const __nv_bfloat16* __restrict__ x, const __nv_bfloat16* __restrict__ kc,
                    const __nv_bfloat16* __restrict__ vc, const __nv_bfloat16* __restrict__ wq,
                    const __nv_bfloat16* __restrict__ wo, const __nv_bfloat16* __restrict__ w1,
                    const __nv_bfloat16* __restrict__ b1, const __nv_bfloat16* __restrict__ w2,
                    const __nv_bfloat16* __restrict__ gw, __nv_bfloat16* __restrict__ out) {
    extern __shared__ __align__(128) unsigned char smem[];
    const uint32_t sb = smem_u32(smem);
    const int cta = blockIdx.x;
    const int kvh = cta >> 4, r = cta & 15;
    const int hj = cta >> 2, cq = cta & 3;
    const uint32_t bar0 = sb + OFF_BAR;

    if (threadIdx.x < NLOAD) {
        const int lt = threadIdx.x;
        PROF_DECL;
        PROF_T(16);
        burst<4, 32 * HQD * 2>(sb + OFF_WQ + (lt >> 2) * 64 + (((lt & 3) ^ ((lt >> 3) & 3)) << 4),
                               (const char*)wq + (size_t)(lt >> 2) * (HQD * 2) + cta * 64 + (lt & 3) * 16);
        if (cta < 112)
            burst<2, 64 * FF * 2>(sb + OFF_W1 + (lt >> 1) * 32 + (((lt & 1) ^ ((lt >> 3) & 1)) << 4),
                                  (const char*)w1 + (size_t)(lt >> 1) * (FF * 2) + cta * 32 + (lt & 1) * 16);
        asm volatile("cp.async.commit_group;" ::: "memory");
        const uint32_t t0 = gtime32();
        if (lt <= BAR_FREE) mbar_init(bar0 + 8 * lt, lt == BAR_FREE ? 8 : NLOAD);
        asm volatile("bar.sync 2, 128;\nbar.arrive 0, 384;" ::: "memory");
        cp_arrive(bar0 + 8 * BAR_WQ);
        const int row = lt >> 4, c = lt & 15;
        const uint32_t sw = sb + row * 256 + ((c ^ row) << 4);
        const size_t kvoff = ((size_t)((r >> 2) * 8 + kvh) * SK + (SK - WIN) + (r & 3) * 256) * 256 + lt * 16;
        int due = T_K;
        stream<8, 2048, TAU_NS>(t0, due, sw + OFF_K, (const char*)kc + kvoff);
        cp_arrive(bar0 + 8 * BAR_K);
        PROF_T(17);
#pragma unroll 1
        for (int ch = 0; ch < 4; ch++) {
            stream<2, 2048, TAU_NS>(t0, due, sw + OFF_V + ch * 16384, (const char*)vc + kvoff + ch * 16384);
            cp_arrive(bar0 + 8 * (BAR_V0 + ch));
        }
        PROF_T(18);
        mbar_wait(bar0 + 8 * BAR_FREE);
        const int wofs = row * (DM * 2) + cq * 256 + c * 16;
        {
            const char* src = (const char*)w2 + hj * (56 * DM * 2) + wofs;
            paced_unit<4, 8 * DM * 2, TAU_TAIL>(t0, due, sw + OFF_W2, src);
            paced_unit<3, 8 * DM * 2, TAU_TAIL>(t0, due, sw + OFF_W2 + 4 * 2048, src + 4 * 8 * DM * 2);
            cp_arrive(bar0 + 8 * BAR_W2);
        }
        {
            const char* src = (const char*)wo + hj * (128 * DM * 2) + wofs;
#pragma unroll 1
            for (int u = 0; u < 4; u++) {
                paced_unit<4, 8 * DM * 2, TAU_TAIL>(t0, due, sw + OFF_WO + u * 8192, src + u * (32 * DM * 2));
                if (u >= 1) cp_arrive(bar0 + 8 * (BAR_WO0 + u - 1));
            }
        }
        PROF_T(19);
        asm volatile("cp.async.wait_all;" ::: "memory");
        PROF_T(20);
        if (lt == 0) PROF_DUMP(16, 5);
        return;
    }

    const int tid = threadIdx.x - NLOAD;
    const int lane = tid & 31, w = tid >> 5;
    const int g = lane >> 2, t = lane & 3;
    const int t1 = t & 1, th = t >> 1;
    const int mi = lane >> 3, l8 = lane & 7;
    const int ab = r >> 2;
    PROF_DECL;
    PROF_T(0);
    float* const part = reinterpret_cast<float*>(smem + OFF_PART);
    float* const wmax = reinterpret_cast<float*>(smem + OFF_RED);
    float* const wsum = wmax + 32;
    float* const gpart = wmax + 64;
    unsigned long long* const mail = g_mail + MAIL_OFF_WORDS;

    const uint4 xv = __ldg(reinterpret_cast<const uint4*>(x) + tid);
    const uint4 gv = __ldg(reinterpret_cast<const uint4*>(gw) + (tid & 63));
    const uint32_t epoch = *(volatile unsigned int*)&mail[MB_EP + cta] + 1u;
    const uint32_t b1v = __ldg(reinterpret_cast<const uint32_t*>(b1 + (cta < 112 ? cta : 0) * 16) + (tid & 7));
    const int hb = 2 * t1 + th;
    unsigned long long* const ox_slot = mail + MB_OX + ((kvh * 4 + hb) * 16 + r) * 64 + w * 8 + g;
    unsigned long long* e4_slot = mail + MB_E4 + (((hb * 8 + w) * 4 + cq) * 32 + hj) * 16 + g;
    const unsigned long long* ep = mail + MB_E4 + cta * 512 + w * 64 + lane;
    __nv_bfloat16* outp = out + (hj >> 3) * DM + cq * 128 + (hj & 7) * 16 + (tid & 15);
    uint32_t fin_st = sb + OFF_PART + (w * 16 + (lane & 15)) * 4, fin_ld = sb + OFF_PART + (tid & 15) * 4;
    asm volatile("" : "+l"(e4_slot), "+l"(ep), "+l"(outp), "+r"(fin_st), "+r"(fin_ld));
    ll_store(ox_slot, 0u, 0u);
    if (tid < 64) ll_store(mail + MB_QX + (kvh * 4 + (tid >> 4)) * 256 + r * 16 + (tid & 15), 0u, 0u);
    if (tid < 16 && t == cq) ll_store(mail + MB_LX + cta * 16 + g, 0u, 0u);
    ll_store(e4_slot, 0u, 0u);
    ll_store(e4_slot + 8, 0u, 0u);
    *reinterpret_cast<uint4*>(smem + OFF_XS + (tid >> 6) * 1040 + (tid & 63) * 16) = xv;
    {
        float acc = dot2(xv.w, gv.w, dot2(xv.z, gv.z, dot2(xv.y, gv.y, dot2(xv.x, gv.x, 0.f))));
#pragma unroll
        for (int o = 16; o > 0; o >>= 1) acc += __shfl_xor_sync(0xffffffffu, acc, o);
        if (lane == 0) gpart[w] = acc;
    }
    asm volatile("bar.sync 0, 384;" ::: "memory");
    PROF_T(1);

    {
        uint32_t xb[2][4];
        const uint32_t xa = sb + OFF_XS + (l8 & 3) * 1040 + (w * 64 + mi * 8) * 2;
        ldsm4(xb[0], xa);
        ldsm4(xb[1], xa + 64);
        const int kr = w * 64 + l8 + ((mi >> 1) << 3);
        const uint32_t aq0 = sb + OFF_WQ + kr * 64 + (((mi & 1) ^ ((kr >> 1) & 3)) << 4);
        const uint32_t aq1 = aq0 ^ 32;
        const uint32_t ah = sb + OFF_W1 + kr * 32 + (((mi & 1) ^ ((kr >> 2) & 1)) << 4);
        float cq0[4] = {0.f, 0.f, 0.f, 0.f}, cq1[4] = {0.f, 0.f, 0.f, 0.f}, ch[4] = {0.f, 0.f, 0.f, 0.f};
        mbar_wait(bar0 + 8 * BAR_WQ);
        PROF_T(2);
#pragma unroll
        for (int ks = 0; ks < 4; ks++) {
            uint32_t a0[4], a1[4], a2[4];
            ldsm4t(a0, aq0 + ks * 1024);
            ldsm4t(a1, aq1 + ks * 1024);
            ldsm4t(a2, ah + ks * 512);
            const uint32_t bb0 = xb[ks >> 1][(ks & 1) * 2], bb1 = xb[ks >> 1][(ks & 1) * 2 + 1];
            mma16816(cq0, a0, bb0, bb1);
            mma16816(cq1, a1, bb0, bb1);
            mma16816(ch, a2, bb0, bb1);
        }
        __syncwarp();
        if (lane == 0) mbar_arrive(bar0 + 8 * BAR_FREE);
        if (t < 2) {
            float* p0 = part + (w * 4 + 2 * t) * 48 + g;
            p0[0] = cq0[0]; p0[48] = cq0[1]; p0[8] = cq0[2]; p0[56] = cq0[3];
            p0[16] = cq1[0]; p0[64] = cq1[1]; p0[24] = cq1[2]; p0[72] = cq1[3];
            p0[32] = ch[0]; p0[80] = ch[1]; p0[40] = ch[2]; p0[88] = ch[3];
        }
        bar_comp();
        if (tid < 96) {
            const bool isq = tid < 64;
            const int b = isq ? tid >> 4 : (tid - 64) >> 3;
            const int cp = isq ? tid & 15 : 16 + (tid & 7);
            float v0 = 0.f, v1 = 0.f;
#pragma unroll
            for (int i = 0; i < 8; i++) {
                const float2 v = *reinterpret_cast<const float2*>(part + (i * 4 + b) * 48 + 2 * cp);
                v0 += v.x; v1 += v.y;
            }
            if (!isq) { v0 = mish(v0 + bf_lo(b1v)); v1 = mish(v1 + bf_hi(b1v)); }
            const int slot = isq ? MB_QX + (kvh * 4 + b) * 256 + r * 16 + cp : MB_AX + cta * 32 + (tid - 64);
            if (isq || cta < 112) ll_store(mail + slot, pack_bf16(v0, v1), epoch);
        }
    }
    PROF_T(3);

    mbar_wait(bar0 + 8 * BAR_K);
    {
        const unsigned long long* qp = mail + MB_QX + (kvh * 4 + ab) * 256 + tid;
        uint2 v[1] = {ll_load(qp)};
        ll_finish<1, 1, BACKOFF_Q>(v, qp, epoch);
        sts32(sb + OFF_QS + (tid >> 6) * 272 + (tid & 63) * 4, v[0].x);
    }
    bar_comp();
    PROF_T(5);

    constexpr float SC = 0.08838834764831845f * LOG2E;
    {
        float s0[4] = {0.f, 0.f, 0.f, 0.f}, s1[4] = {0.f, 0.f, 0.f, 0.f};
        const uint32_t qa = sb + OFF_QS + (l8 & 3) * 272 + mi * 16;
        const uint32_t kb = sb + OFF_K + (w * 32 + (lane & 15)) * 256;
        const int kx = (lane >> 4) ^ l8;
        mbar_wait(bar0 + 8 * BAR_K);
        PROF_T(4);
#pragma unroll
        for (int i = 0; i < 4; i++) {
            uint32_t qb[4], a0[4], a1[4], a2[4], a3[4];
            const uint32_t o0 = (uint32_t)((kx ^ (4 * i)) << 4), o1 = o0 ^ 32;
            ldsm4(qb, qa + i * 64);
            ldsm4(a0, kb + o0);
            ldsm4(a1, kb + 16 * 256 + o0);
            ldsm4(a2, kb + o1);
            ldsm4(a3, kb + 16 * 256 + o1);
            mma16816(s0, a0, qb[0], qb[1]);
            mma16816(s1, a1, qb[0], qb[1]);
            mma16816(s0, a2, qb[2], qb[3]);
            mma16816(s1, a3, qb[2], qb[3]);
        }
        float m0 = fmaxf(fmaxf(s0[0], s0[2]), fmaxf(s1[0], s1[2]));
        float m1 = fmaxf(fmaxf(s0[1], s0[3]), fmaxf(s1[1], s1[3]));
#pragma unroll
        for (int o = 4; o < 32; o <<= 1) {
            m0 = fmaxf(m0, __shfl_xor_sync(0xffffffffu, m0, o));
            m1 = fmaxf(m1, __shfl_xor_sync(0xffffffffu, m1, o));
        }
        if (lane < 2) *reinterpret_cast<float2*>(wmax + w * 4 + 2 * lane) = make_float2(m0, m1);
        bar_comp();
#pragma unroll
        for (int i = 0; i < 8; i++) {
            const float2 v = *reinterpret_cast<const float2*>(wmax + i * 4 + 2 * t1);
            m0 = fmaxf(m0, v.x); m1 = fmaxf(m1, v.y);
        }
        const float n0 = m0 * SC, n1 = m1 * SC;
        const uint32_t pa = pack_bf16(ex2(fmaf(th ? s1[0] : s0[0], SC, -n0)), ex2(fmaf(th ? s1[2] : s0[2], SC, -n0)));
        const uint32_t pb = pack_bf16(ex2(fmaf(th ? s1[1] : s0[1], SC, -n1)), ex2(fmaf(th ? s1[3] : s0[3], SC, -n1)));
        const uint32_t pd = sb + OFF_PS + t1 * (2 * 528) + (w * 32 + th * 16 + g) * 2;
        sts16(pd, pa); sts16(pd + 16, pa >> 16); sts16(pd + 528, pb); sts16(pd + 544, pb >> 16);
        float l0 = bf_lo(pa) + bf_hi(pa), l1 = bf_lo(pb) + bf_hi(pb);
#pragma unroll
        for (int o = 2; o < 32; o <<= 1) {
            l0 += __shfl_xor_sync(0xffffffffu, l0, o);
            l1 += __shfl_xor_sync(0xffffffffu, l1, o);
        }
        if (lane < 2) *reinterpret_cast<float2*>(wsum + w * 4 + 2 * lane) = make_float2(l0, l1);
        bar_comp();
    }
    PROF_T(6);

    const uint32_t a_off = (l8 + ((mi >> 1) << 3)) * 256 + (((2 * w + (mi & 1)) ^ l8) << 4);
    {
        const int hd = (lane >> 2) & 3;
        float l = 0.f, m = wmax[hd];
#pragma unroll
        for (int i = 0; i < 8; i++) { l += wsum[i * 4 + hd]; m = fmaxf(m, wmax[i * 4 + hd]); }
        m *= SC;
        const unsigned long long* lp = mail + MB_LX + ((cta & ~3) + t) * 16 + hd;
        if (tid < 16 && t == cq) ll_store(const_cast<unsigned long long*>(lp), __float_as_uint(m + lg2(l)), epoch);
        if (tid >= 128 && tid < 240) {
            const int b = (tid - 128) / 28, e = tid - 128 - b * 28, ge = hj * 28 + e;
            const unsigned long long* ap = mail + MB_AX + (ge >> 3) * 32 + b * 8 + (ge & 7);
            uint2 av[1] = {ll_load(ap)};
            ll_finish<1, 1, BACKOFF_NS>(av, ap, epoch);
            sts32(sb + OFF_AS + b * 144 + e * 4, av[0].x);
        }
        float o0[4] = {0.f, 0.f, 0.f, 0.f}, o1[4] = {0.f, 0.f, 0.f, 0.f};
        const uint32_t pb = sb + OFF_PS + (l8 & 3) * 528 + mi * 16;
        uint2 lv[1];
        float wgt;
#pragma unroll 1
        for (int ch = 0; ch < 4; ch++) {
            uint32_t pf0[4], pf1[4];
            ldsm4(pf0, pb + ch * 128);
            ldsm4(pf1, pb + ch * 128 + 64);
            if (ch == 2) lv[0] = ll_load(lp);
            if (ch == 3) {
                ll_finish<1, 1, BACKOFF_NS>(lv, lp, epoch);
                const float e = __uint_as_float(lv[0].x);
                float mx = fmaxf(e, __shfl_xor_sync(0xffffffffu, e, 1));
                mx = fmaxf(mx, __shfl_xor_sync(0xffffffffu, mx, 2));
                float den = ex2(e - mx);
                den += __shfl_xor_sync(0xffffffffu, den, 1);
                den += __shfl_xor_sync(0xffffffffu, den, 2);
                wgt = __shfl_sync(0xffffffffu, ex2(m - mx) * rcp(den), hb * 4);
            }
            mbar_wait(bar0 + 8 * (BAR_V0 + ch));
            PROF_T(14);
            mma_tile64(o0, o1, sb + OFF_V + ch * 16384 + a_off, pf0, pf1);
        }
        PROF_T(7);
        const float va = (th ? o0[1] + o1[1] : o0[0] + o1[0]) * wgt;
        const float vb = (th ? o0[3] + o1[3] : o0[2] + o1[2]) * wgt;
        ll_store(ox_slot, pack_bf16(va, vb), epoch);
    }
    PROF_T(8);

    {
        const unsigned long long* op = mail + MB_OX + (hj * 16 + (tid >> 6) * 4) * 64 + (tid & 63);
        uint2 ov[4];
        bar_comp();
        float bq[4] = {0.f, 0.f, 0.f, 0.f}, b2[4] = {0.f, 0.f, 0.f, 0.f};
        {
            uint32_t af0[4], af1[4], f0[4], f1[4], f2[4], f3[4];
            const uint32_t aa = sb + OFF_AS + (l8 & 3) * 144 + mi * 16;
            ldsm4(af0, aa);
            ldsm4(af1, aa + 64);
            mbar_wait(bar0 + 8 * BAR_W2);
            const uint32_t wb = sb + OFF_W2 + a_off;
            ldsm4t(f0, wb);
            ldsm4t(f1, wb + 16 * 256);
            ldsm4t(f2, wb + 32 * 256);
            ldsm4t(f3, wb + 48 * 256);
            mma16816(bq, f0, af0[0], af0[1]);
            mma16816(b2, f1, af0[2], af0[3]);
            mma16816(bq, f2, af1[0], af1[1]);
            mma1688(b2, f3[0], f3[1], af1[2]);
        }
        const float gt = rcp(1.f + ex2(-(gpart[2 * hb] + gpart[2 * hb + 1]) * LOG2E));
        const float rb = (1.f - gt) * (th ? bq[1] + b2[1] : bq[0] + b2[0]);
        const float rd = (1.f - gt) * (th ? bq[3] + b2[3] : bq[2] + b2[2]);
        PROF_T(11);
#pragma unroll
        for (int s = 0; s < 4; s++) ov[s] = ll_load(op + s * 64);
        ll_finish<4, 64, BACKOFF_NS>(ov, op, epoch);
        {
            const float v0 = (bf_lo(ov[0].x) + bf_lo(ov[1].x)) + (bf_lo(ov[2].x) + bf_lo(ov[3].x));
            const float v1 = (bf_hi(ov[0].x) + bf_hi(ov[1].x)) + (bf_hi(ov[2].x) + bf_hi(ov[3].x));
            const uint32_t pk = pack_bf16(v0, v1);
            const uint32_t od = sb + OFF_OS + (tid >> 6) * 272 + (tid & 56) * 4 + (tid & 7) * 2;
            sts16(od, pk); sts16(od + 16, pk >> 16);
        }
        bar_comp();
        PROF_T(9);
        uint32_t of[4][4];
        const uint32_t fb = sb + OFF_OS + (l8 & 3) * 272 + mi * 16;
#pragma unroll
        for (int i = 0; i < 4; i++) ldsm4(of[i], fb + i * 64);
        float a0[4] = {0.f, 0.f, 0.f, 0.f}, a1[4] = {0.f, 0.f, 0.f, 0.f};
        mbar_wait(bar0 + 8 * BAR_WO0);
        mma_tile64(a0, a1, sb + OFF_WO + a_off, of[0], of[1]);
        uint32_t f0[4], f1[4];
        mbar_wait(bar0 + 8 * BAR_WO1);
        ldsm4t(f0, sb + OFF_WO + 64 * 256 + a_off);
        ldsm4t(f1, sb + OFF_WO + 80 * 256 + a_off);
        mma16816(a0, f0, of[2][0], of[2][1]);
        mma16816(a1, f1, of[2][2], of[2][3]);
        mbar_wait(bar0 + 8 * BAR_WO2);
        PROF_T(10);
        ldsm4t(f0, sb + OFF_WO + 96 * 256 + a_off);
        ldsm4t(f1, sb + OFF_WO + 112 * 256 + a_off);
        mma16816(a0, f0, of[3][0], of[3][1]);
        mma16816(a1, f1, of[3][2], of[3][3]);
        ll_store(e4_slot,     __float_as_uint(fmaf(gt, th ? a0[1] + a1[1] : a0[0] + a1[0], rb)), epoch);
        ll_store(e4_slot + 8, __float_as_uint(fmaf(gt, th ? a0[3] + a1[3] : a0[2] + a1[2], rd)), epoch);
    }
    PROF_T(12);

    {
        uint2 v[2];
        {
            uint2 pa[NPOLL], pb[NPOLL];
#pragma unroll
            for (int i = 0; i < NPOLL; i++) {
                const uint32_t c0 = (uint32_t)clock();
                pa[i] = ll_load(ep);
                pb[i] = ll_load(ep + 32);
                if (i + 1 < NPOLL) while ((uint32_t)clock() - c0 < POLL_GAP) {}
            }
#pragma unroll 1
            for (int it = 0; it < SPIN_LIMIT; it++) {
                bool done = false;
#pragma unroll
                for (int i = 0; i < NPOLL; i++) {
                    if (!done) {
                        if (__all_sync(0xffffffffu, pa[i].y == epoch && pb[i].y == epoch)) { v[0] = pa[i]; v[1] = pb[i]; done = true; }
                        else { pa[i] = ll_load(ep); pb[i] = ll_load(ep + 32); }
                    }
                }
                if (done) break;
            }
        }
        PROF_T(15);
        float acc = __uint_as_float(v[0].x) + __uint_as_float(v[1].x);
        acc += __shfl_xor_sync(0xffffffffu, acc, 16);
        if (lane < 16) sts32(fin_st, __float_as_uint(acc));
        bar_comp();
        if (tid < 16) {
            float p[8];
#pragma unroll
            for (int i = 0; i < 8; i++) asm volatile("ld.shared.f32 %0, [%1];" : "=f"(p[i]) : "r"(fin_ld + i * 64) : "memory");
            *outp = __float2bfloat16(((p[0] + p[1]) + (p[2] + p[3])) + ((p[4] + p[5]) + (p[6] + p[7])));
            if (tid == 0) *(volatile unsigned int*)&mail[MB_EP + cta] = epoch;
        }
        PROF_T(13);
        if (tid == 0) PROF_DUMP(0, 16);
    }
}

}

extern "C" void kernel_launch(void* const* d_in, const int* in_sizes, int n_in, void* d_out, int out_size) {
    (void)in_sizes; (void)n_in; (void)out_size;
    const __nv_bfloat16* x  = (const __nv_bfloat16*)d_in[0];
    const __nv_bfloat16* kc = (const __nv_bfloat16*)d_in[1];
    const __nv_bfloat16* vc = (const __nv_bfloat16*)d_in[2];
    const __nv_bfloat16* wq = (const __nv_bfloat16*)d_in[3];
    const __nv_bfloat16* wo = (const __nv_bfloat16*)d_in[4];
    const __nv_bfloat16* w1 = (const __nv_bfloat16*)d_in[6];
    const __nv_bfloat16* b1 = (const __nv_bfloat16*)d_in[7];
    const __nv_bfloat16* w2 = (const __nv_bfloat16*)d_in[8];
    const __nv_bfloat16* gw = (const __nv_bfloat16*)d_in[9];
    cudaFuncSetAttribute(fused_decode_kernel, cudaFuncAttributeMaxDynamicSharedMemorySize, SMEM_BYTES);
    fused_decode_kernel<<<NCTA, NTHREADS, SMEM_BYTES, cudaStreamPerThread>>>(x, kc, vc, wq, wo, w1, b1, w2, gw,
                                                                            (__nv_bfloat16*)d_out);
}
```

```cpp
#include <cuda_runtime.h>
#include <cuda_bf16.h>
#include <stdint.h>

namespace {

constexpr int NCTA     = 128;
constexpr int NCOMP    = 256;
constexpr int NLOAD    = 128;
constexpr int NTHREADS = NCOMP + NLOAD;
#define WINDOW 8
#define TAU_TAIL TAU_NS
#define TAU_NS 84
#define T_K 1600
#define INIT_SLOTS 1
#define BACKOFF_NS 64
#define LOADER_FIRST 1
#define LOADER_INLINE __forceinline__
#define KV_INTERLEAVE 0
#define EVICT_FIRST 1
#define O_EARLY 0
#define Q_LATE 1
#define NPOLL 2
#define POLL_GAP 80
#define BACKOFF_E4 0
#define BACKOFF_Q 200
constexpr int SPIN_LIMIT = 1 << 20;

constexpr int DM = 512, HQD = 4096, SK = 4096, WIN = 1024, FF = 1792;

constexpr int OFF_WQ   = 0;
constexpr int OFF_W1   = 32768;
constexpr int OFF_WO   = OFF_WQ;
constexpr int OFF_W2   = OFF_W1;
constexpr int OFF_K    = 49152;
constexpr int OFF_V    = OFF_K + 65536;
constexpr int OFF_XS   = OFF_V + 65536;
constexpr int OFF_PART = OFF_XS + 4 * 1040;
constexpr int OFF_QS   = OFF_PART + 6144;
constexpr int OFF_PS   = OFF_QS + 4 * 272;
constexpr int OFF_OS   = OFF_PS + 4 * 528;
constexpr int OFF_AS   = OFF_OS + 4 * 272;
constexpr int OFF_RED  = OFF_AS + 4 * 144;
constexpr int OFF_BAR  = OFF_RED + 320;
constexpr int SMEM_BYTES = OFF_BAR + 128;

enum { BAR_WQ = 0, BAR_K = 1, BAR_V0 = 2, BAR_W2 = 6, BAR_WO0 = 7, BAR_WO1 = 8, BAR_WO2 = 9, BAR_FREE = 10 };

constexpr int MB_QX = 0;
constexpr int MB_AX = MB_QX + 8 * 4 * 256;
constexpr int MB_LX = MB_AX + 112 * 32;
constexpr int MB_OX = MB_LX + NCTA * 16;
constexpr int MB_E4 = MB_OX + 32 * 16 * 64;
constexpr int MB_EP = MB_E4 + NCTA * 512;
constexpr int MB_WORDS = MB_EP + NCTA;
#define MAIL_PAD_WORDS 0
#define MAIL_OFF_WORDS 0
__device__ __align__(128) unsigned long long g_mail[MB_WORDS + MAIL_PAD_WORDS];
#define PROF_DECL
#define PROF_T(i) do {} while (0)
#define PROF_DUMP(base, n) do {} while (0)

__device__ __forceinline__ uint32_t smem_u32(const void* p) { return (uint32_t)__cvta_generic_to_shared(p); }
__device__ __forceinline__ void mbar_init(uint32_t bar, uint32_t cnt) {
    asm volatile("mbarrier.init.shared::cta.b64 [%0], %1;" ::"r"(bar), "r"(cnt) : "memory");
}
__device__ __forceinline__ void mbar_arrive(uint32_t bar) {
    asm volatile("mbarrier.arrive.shared::cta.b64 _, [%0];" ::"r"(bar) : "memory");
}
__device__ __forceinline__ void mbar_wait(uint32_t bar) {
    asm volatile("{\n.reg .pred p;\nW_%=:\nmbarrier.try_wait.parity.shared::cta.b64 p, [%0], 0;\n@!p bra W_%=;\n}" ::"r"(bar) : "memory");
}
__device__ __forceinline__ void cp_arrive(uint32_t bar) {
    asm volatile("cp.async.mbarrier.arrive.noinc.shared::cta.b64 [%0];" ::"r"(bar) : "memory");
}
template <int N, int SSTRIDE, int J = 0>
__device__ __forceinline__ void cp_steps(uint32_t dst, const char* src) {
    if constexpr (J < N) {
        asm volatile("{\n.reg .b64 pol;\ncreatepolicy.fractional.L2::evict_first.b64 pol, 1.0;\n"
                     "cp.async.cg.shared.global.L2::cache_hint [%0 + %2], [%1 + %3], 16, pol;\n}"
                     ::"r"(dst), "l"(src), "n"(J * 2048), "n"(J * SSTRIDE) : "memory");
        cp_steps<N, SSTRIDE, J + 1>(dst, src);
    }
}
template <int UNITS, int SSTRIDE>
__device__ __forceinline__ void burst(uint32_t dst, const char* src) {
#pragma unroll 1
    for (int i = 0; i < UNITS; i++) {
        cp_steps<4, SSTRIDE>(dst, src);
        dst += 4 * 2048;
        src += 4 * SSTRIDE;
    }
}
__device__ __forceinline__ uint32_t gtime32() { uint32_t t; asm volatile("mov.u32 %0, %%globaltimer_lo;" : "=r"(t)); return t; }
template <int N, int SSTRIDE, int TAU>
__device__ __forceinline__ void paced_unit(uint32_t t0, int& due, uint32_t dst, const char* src) {
    if (TAU > 0) {
        while ((int)(gtime32() - t0) < due) {}
        due += N * TAU;
    }
    cp_steps<N, SSTRIDE>(dst, src);
    asm volatile("cp.async.commit_group;\ncp.async.wait_group %0;" ::"n"(WINDOW - 1) : "memory");
}
template <int UNITS, int SSTRIDE, int USTRIDE, int TAU>
__device__ __forceinline__ void stream(uint32_t t0, int& due, uint32_t dst, const char* src) {
#pragma unroll 1
    for (int i = 0; i < UNITS; i++) {
        paced_unit<4, SSTRIDE, TAU>(t0, due, dst, src);
        dst += 4 * 2048;
        src += USTRIDE;
    }
}
__device__ __forceinline__ void bar_comp() { asm volatile("bar.sync 1, 256;" ::: "memory"); }

__device__ __forceinline__ void ldsm4(uint32_t (&r)[4], uint32_t a) {
    asm volatile("ldmatrix.sync.aligned.m8n8.x4.shared.b16 {%0,%1,%2,%3}, [%4];"
                 : "=r"(r[0]), "=r"(r[1]), "=r"(r[2]), "=r"(r[3]) : "r"(a) : "memory");
}
__device__ __forceinline__ void ldsm4t(uint32_t (&r)[4], uint32_t a) {
    asm volatile("ldmatrix.sync.aligned.m8n8.x4.trans.shared.b16 {%0,%1,%2,%3}, [%4];"
                 : "=r"(r[0]), "=r"(r[1]), "=r"(r[2]), "=r"(r[3]) : "r"(a) : "memory");
}
__device__ __forceinline__ void mma16816(float (&c)[4], const uint32_t (&a)[4], uint32_t b0, uint32_t b1) {
    asm volatile("mma.sync.aligned.m16n8k16.row.col.f32.bf16.bf16.f32 {%0,%1,%2,%3}, {%4,%5,%6,%7}, {%8,%9}, {%0,%1,%2,%3};"
                 : "+f"(c[0]), "+f"(c[1]), "+f"(c[2]), "+f"(c[3])
                 : "r"(a[0]), "r"(a[1]), "r"(a[2]), "r"(a[3]), "r"(b0), "r"(b1));
}
__device__ __forceinline__ void mma1688(float (&c)[4], uint32_t a0, uint32_t a1, uint32_t b0) {
    asm volatile("mma.sync.aligned.m16n8k8.row.col.f32.bf16.bf16.f32 {%0,%1,%2,%3}, {%4,%5}, {%6}, {%0,%1,%2,%3};"
                 : "+f"(c[0]), "+f"(c[1]), "+f"(c[2]), "+f"(c[3])
                 : "r"(a0), "r"(a1), "r"(b0));
}
__device__ __forceinline__ void mma_tile64(float (&c0)[4], float (&c1)[4], uint32_t a, const uint32_t (&b0)[4], const uint32_t (&b1)[4]) {
    uint32_t f0[4], f1[4], f2[4], f3[4];
    ldsm4t(f0, a);
    ldsm4t(f1, a + 16 * 256);
    ldsm4t(f2, a + 32 * 256);
    ldsm4t(f3, a + 48 * 256);
    mma16816(c0, f0, b0[0], b0[1]);
    mma16816(c1, f1, b0[2], b0[3]);
    mma16816(c0, f2, b1[0], b1[1]);
    mma16816(c1, f3, b1[2], b1[3]);
}
__device__ __forceinline__ uint32_t pack_bf16(float lo, float hi) {
    uint32_t r;
    asm("cvt.rn.bf16x2.f32 %0, %1, %2;" : "=r"(r) : "f"(hi), "f"(lo));
    return r;
}
__device__ __forceinline__ float bf_lo(uint32_t v) { return __uint_as_float(v << 16); }
__device__ __forceinline__ float bf_hi(uint32_t v) { return __uint_as_float(v & 0xffff0000u); }
__device__ __forceinline__ float ex2(float x) { float y; asm("ex2.approx.ftz.f32 %0, %1;" : "=f"(y) : "f"(x)); return y; }
__device__ __forceinline__ float lg2(float x) { float y; asm("lg2.approx.ftz.f32 %0, %1;" : "=f"(y) : "f"(x)); return y; }
__device__ __forceinline__ float rcp(float x) { float y; asm("rcp.approx.ftz.f32 %0, %1;" : "=f"(y) : "f"(x)); return y; }
__device__ __forceinline__ float dot2(uint32_t a, uint32_t b, float acc) {
    return fmaf(bf_hi(a), bf_hi(b), fmaf(bf_lo(a), bf_lo(b), acc));
}
__device__ __forceinline__ void sts32(uint32_t a, uint32_t v) { asm volatile("st.shared.b32 [%0], %1;" ::"r"(a), "r"(v) : "memory"); }
__device__ __forceinline__ void sts16(uint32_t a, uint32_t v) { asm volatile("st.shared.b16 [%0], %1;" ::"r"(a), "h"((unsigned short)v) : "memory"); }

__device__ __forceinline__ void ll_store(unsigned long long* p, uint32_t payload, uint32_t epoch) {
    asm volatile("{\n.reg .b64 v;\nmov.b64 v, {%1, %2};\nst.relaxed.gpu.global.b64 [%0], v;\n}" ::"l"(p), "r"(payload), "r"(epoch) : "memory");
}
__device__ __forceinline__ uint2 ll_load(const unsigned long long* p) {
    uint2 v;
    asm volatile("{\n.reg .b64 v;\nld.relaxed.gpu.global.b64 v, [%2];\nmov.b64 {%0, %1}, v;\n}" : "=r"(v.x), "=r"(v.y) : "l"(p) : "memory");
    return v;
}
template <int N, int STRIDE, int SLEEP>
__device__ __forceinline__ void ll_finish(uint2 (&v)[N], const unsigned long long* p, uint32_t epoch) {
#pragma unroll 1
    for (int it = 0; it < SPIN_LIMIT; it++) {
        bool ok = true;
#pragma unroll
        for (int i = 0; i < N; i++) ok = ok && v[i].y == epoch;
        if (__all_sync(0xffffffffu, ok)) break;
        if (SLEEP) __nanosleep(SLEEP);
#pragma unroll
        for (int i = 0; i < N; i++)
            if (v[i].y != epoch) v[i] = ll_load(p + i * STRIDE);
    }
}

constexpr float LOG2E = 1.4426950408889634f;
__device__ __forceinline__ float mish(float h) {
    const float e = ex2(-fabsf(h) * LOG2E);
    const float num = h >= 0.f ? fmaf(2.f, e, 1.f) : e * (e + 2.f);
    const float den = num + (h >= 0.f ? 2.f * e * e : 2.f);
    return h * num * rcp(den);
}

__device__ LOADER_INLINE void loader(const __nv_bfloat16* __restrict__ kc, const __nv_bfloat16* __restrict__ vc,
                                    const __nv_bfloat16* __restrict__ wq, const __nv_bfloat16* __restrict__ wo,
                                    const __nv_bfloat16* __restrict__ w1, const __nv_bfloat16* __restrict__ w2, uint32_t sb) {
    const int cta = blockIdx.x;
    const int kvh = cta >> 4, r = cta & 15;
    const int hj = cta >> 2, cq = cta & 3;
    const uint32_t bar0 = sb + OFF_BAR;
    {
        const int lt = LOADER_FIRST ? threadIdx.x : threadIdx.x - NCOMP;
        PROF_DECL;
        PROF_T(16);
        const uint32_t t0 = gtime32();
        burst<4, 32 * HQD * 2>(sb + OFF_WQ + (lt >> 2) * 64 + (((lt & 3) ^ ((lt >> 3) & 3)) << 4),
                               (const char*)wq + (size_t)(lt >> 2) * (HQD * 2) + cta * 64 + (lt & 3) * 16);
        if (cta < 112)
            burst<2, 64 * FF * 2>(sb + OFF_W1 + (lt >> 1) * 32 + (((lt & 1) ^ ((lt >> 3) & 1)) << 4),
                                  (const char*)w1 + (size_t)(lt >> 1) * (FF * 2) + cta * 32 + (lt & 1) * 16);
        asm volatile("cp.async.commit_group;" ::: "memory");
        if (lt <= BAR_FREE) mbar_init(bar0 + 8 * lt, lt == BAR_FREE ? 8 : NLOAD);
        asm volatile("bar.sync 2, 128;\nbar.arrive 0, 384;" ::: "memory");
        const int row = lt >> 4, c = lt & 15;
        const uint32_t sw = sb + row * 256 + ((c ^ row) << 4);
        constexpr int KVU = KV_INTERLEAVE ? 4 * 8192 : 8192;
        const size_t kvoff = ((size_t)((r >> 2) * 8 + kvh) * SK + (SK - WIN)) * 256 + (r & 3) * (KV_INTERLEAVE ? 8192 : 65536) + lt * 16;
        int due = T_K;
        cp_arrive(bar0 + 8 * BAR_WQ);
        {
            uint32_t dst = sw + OFF_K;
            const char* src = (const char*)kc + kvoff;
#pragma unroll 1
            for (int u = 0; u < 16; u++) {
                paced_unit<4, 2048, TAU_NS>(t0, due, dst, src);
                dst += 8192;
                src = u == 7 ? (const char*)vc + kvoff : src + KVU;
                if (u >= 7 && (u & 1)) cp_arrive(bar0 + 8 * (BAR_K + ((u - 7) >> 1)));
            }
        }
        PROF_T(18);
        mbar_wait(bar0 + 8 * BAR_FREE);
        const int wofs = row * (DM * 2) + cq * 256 + c * 16;
        {
            const char* src = (const char*)w2 + hj * (56 * DM * 2) + wofs;
            paced_unit<4, 8 * DM * 2, TAU_TAIL>(t0, due, sw + OFF_W2, src);
            paced_unit<3, 8 * DM * 2, TAU_TAIL>(t0, due, sw + OFF_W2 + 4 * 2048, src + 4 * 8 * DM * 2);
            cp_arrive(bar0 + 8 * BAR_W2);
        }
        {
            const char* src = (const char*)wo + hj * (128 * DM * 2) + wofs;
#pragma unroll 1
            for (int u = 0; u < 4; u++) {
                paced_unit<4, 8 * DM * 2, TAU_TAIL>(t0, due, sw + OFF_WO + u * 8192, src + u * (32 * DM * 2));
                if (u >= 1) cp_arrive(bar0 + 8 * (BAR_WO0 + u - 1));
            }
        }
        PROF_T(19);
        asm volatile("cp.async.wait_all;" ::: "memory");
        PROF_T(20);
        if (lt == 0) PROF_DUMP(16, 5);
    }
}

__global__ void __launch_bounds__(NTHREADS, 1)
fused_decode_kernel(const __nv_bfloat16* __restrict__ x, const __nv_bfloat16* __restrict__ kc,
                    const __nv_bfloat16* __restrict__ vc, const __nv_bfloat16* __restrict__ wq,
                    const __nv_bfloat16* __restrict__ wo, const __nv_bfloat16* __restrict__ w1,
                    const __nv_bfloat16* __restrict__ b1, const __nv_bfloat16* __restrict__ w2,
                    const __nv_bfloat16* __restrict__ gw, __nv_bfloat16* __restrict__ out) {
    extern __shared__ __align__(128) unsigned char smem[];
    const uint32_t sb = smem_u32(smem);
    const int cta = blockIdx.x;
    const int kvh = cta >> 4, r = cta & 15;
    const int hj = cta >> 2, cq = cta & 3;
    const uint32_t bar0 = sb + OFF_BAR;

    if (LOADER_FIRST ? threadIdx.x < NLOAD : threadIdx.x >= NCOMP) {
        loader(kc, vc, wq, wo, w1, w2, sb);
        return;
    }

    const int tid = LOADER_FIRST ? threadIdx.x - NLOAD : threadIdx.x;
    const int lane = tid & 31, w = tid >> 5;
    const int g = lane >> 2, t = lane & 3;
    const int t1 = t & 1, th = t >> 1;
    const int mi = lane >> 3, l8 = lane & 7;
    const int ab = r >> 2;
    PROF_DECL;
    PROF_T(0);
    float* const part = reinterpret_cast<float*>(smem + OFF_PART);
    float* const wmax = reinterpret_cast<float*>(smem + OFF_RED);
    float* const wsum = wmax + 32;
    float* const gpart = wmax + 64;
    unsigned long long* const mail = g_mail + MAIL_OFF_WORDS;

    const uint4 xv = __ldg(reinterpret_cast<const uint4*>(x) + tid);
    const uint4 gv = __ldg(reinterpret_cast<const uint4*>(gw) + (tid & 63));
    const uint32_t epoch = *(volatile unsigned int*)&mail[MB_EP + cta] + 1u;
    const uint32_t b1v = __ldg(reinterpret_cast<const uint32_t*>(b1 + (cta < 112 ? cta : 0) * 16) + (tid & 7));
    const int hb = 2 * t1 + th;
    unsigned long long* const ox_slot = mail + MB_OX + ((kvh * 4 + hb) * 16 + r) * 64 + w * 8 + g;
    unsigned long long* e4_slot = mail + MB_E4 + (((hb * 8 + w) * 4 + cq) * 32 + hj) * 16 + g;
    const unsigned long long* ep = mail + MB_E4 + cta * 512 + w * 64 + lane;
    __nv_bfloat16* outp = out + (hj >> 3) * DM + cq * 128 + (hj & 7) * 16 + (tid & 15);
    uint32_t fin_st = sb + OFF_PART + (w * 16 + (lane & 15)) * 4, fin_ld = sb + OFF_PART + (tid & 15) * 4;
    asm volatile("" : "+l"(e4_slot), "+l"(ep), "+l"(outp), "+r"(fin_st), "+r"(fin_ld));
    *reinterpret_cast<uint4*>(smem + OFF_XS + (tid >> 6) * 1040 + (tid & 63) * 16) = xv;
    {
        float acc = dot2(xv.w, gv.w, dot2(xv.z, gv.z, dot2(xv.y, gv.y, dot2(xv.x, gv.x, 0.f))));
#pragma unroll
        for (int o = 16; o > 0; o >>= 1) acc += __shfl_xor_sync(0xffffffffu, acc, o);
        if (lane == 0) gpart[w] = acc;
    }
    asm volatile("bar.sync 0, 384;" ::: "memory");
    PROF_T(1);
    ll_store(ox_slot, 0u, 0u);
    if (tid < 16 && t == cq) ll_store(mail + MB_LX + cta * 16 + g, 0u, 0u);
    ll_store(e4_slot, 0u, 0u);
    ll_store(e4_slot + 8, 0u, 0u);

    {
        uint32_t xb[2][4];
        const uint32_t xa = sb + OFF_XS + (l8 & 3) * 1040 + (w * 64 + mi * 8) * 2;
        ldsm4(xb[0], xa);
        ldsm4(xb[1], xa + 64);
        const int kr = w * 64 + l8 + ((mi >> 1) << 3);
        const uint32_t aq0 = sb + OFF_WQ + kr * 64 + (((mi & 1) ^ ((kr >> 1) & 3)) << 4);
        const uint32_t aq1 = aq0 ^ 32;
        const uint32_t ah = sb + OFF_W1 + kr * 32 + (((mi & 1) ^ ((kr >> 2) & 1)) << 4);
        float cq0[4] = {0.f, 0.f, 0.f, 0.f}, cq1[4] = {0.f, 0.f, 0.f, 0.f}, ch[4] = {0.f, 0.f, 0.f, 0.f};
        mbar_wait(bar0 + 8 * BAR_WQ);
        PROF_T(2);
#pragma unroll
        for (int ks = 0; ks < 4; ks++) {
            uint32_t a0[4], a1[4], a2[4];
            ldsm4t(a0, aq0 + ks * 1024);
            ldsm4t(a1, aq1 + ks * 1024);
            ldsm4t(a2, ah + ks * 512);
            const uint32_t bb0 = xb[ks >> 1][(ks & 1) * 2], bb1 = xb[ks >> 1][(ks & 1) * 2 + 1];
            mma16816(cq0, a0, bb0, bb1);
            mma16816(cq1, a1, bb0, bb1);
            mma16816(ch, a2, bb0, bb1);
        }
        __syncwarp();
        if (lane == 0) mbar_arrive(bar0 + 8 * BAR_FREE);
        if (t < 2) {
            float* p0 = part + (w * 4 + 2 * t) * 48 + g;
            p0[0] = cq0[0]; p0[48] = cq0[1]; p0[8] = cq0[2]; p0[56] = cq0[3];
            p0[16] = cq1[0]; p0[64] = cq1[1]; p0[24] = cq1[2]; p0[72] = cq1[3];
            p0[32] = ch[0]; p0[80] = ch[1]; p0[40] = ch[2]; p0[88] = ch[3];
        }
        bar_comp();
        if (tid < 96) {
            const bool isq = tid < 64;
            const int b = isq ? tid >> 4 : (tid - 64) >> 3;
            const int cp = isq ? tid & 15 : 16 + (tid & 7);
            float v0 = 0.f, v1 = 0.f;
#pragma unroll
            for (int i = 0; i < 8; i++) {
                const float2 v = *reinterpret_cast<const float2*>(part + (i * 4 + b) * 48 + 2 * cp);
                v0 += v.x; v1 += v.y;
            }
            if (!isq) { v0 = mish(v0 + bf_lo(b1v)); v1 = mish(v1 + bf_hi(b1v)); }
            const int slot = isq ? MB_QX + (kvh * 4 + b) * 256 + r * 16 + cp : MB_AX + cta * 32 + (tid - 64);
            if (isq || cta < 112) ll_store(mail + slot, pack_bf16(v0, v1), epoch);
        }
    }
    PROF_T(3);

    mbar_wait(bar0 + 8 * BAR_K);
    {
        const unsigned long long* qp = mail + MB_QX + (kvh * 4 + ab) * 256 + tid;
        uint2 v[1] = {ll_load(qp)};
        ll_finish<1, 1, BACKOFF_Q>(v, qp, epoch);
        sts32(sb + OFF_QS + (tid >> 6) * 272 + (tid & 63) * 4, v[0].x);
    }
    bar_comp();
    PROF_T(5);

    constexpr float SC = 0.08838834764831845f * LOG2E;
    {
        float s0[4] = {0.f, 0.f, 0.f, 0.f}, s1[4] = {0.f, 0.f, 0.f, 0.f};
        const uint32_t qa = sb + OFF_QS + (l8 & 3) * 272 + mi * 16;
        const uint32_t kb = sb + OFF_K + (w * 32 + (lane & 15)) * 256;
        const int kx = (lane >> 4) ^ l8;
        mbar_wait(bar0 + 8 * BAR_K);
        PROF_T(4);
#pragma unroll 1
        for (int i = 0; i < 4; i++) {
            uint32_t qb[4], a0[4], a1[4], a2[4], a3[4];
            const uint32_t o0 = (uint32_t)((kx ^ (4 * i)) << 4), o1 = o0 ^ 32;
            ldsm4(qb, qa + i * 64);
            ldsm4(a0, kb + o0);
            ldsm4(a1, kb + 16 * 256 + o0);
            ldsm4(a2, kb + o1);
            ldsm4(a3, kb + 16 * 256 + o1);
            mma16816(s0, a0, qb[0], qb[1]);
            mma16816(s1, a1, qb[0], qb[1]);
            mma16816(s0, a2, qb[2], qb[3]);
            mma16816(s1, a3, qb[2], qb[3]);
        }
        float m0 = fmaxf(fmaxf(s0[0], s0[2]), fmaxf(s1[0], s1[2]));
        float m1 = fmaxf(fmaxf(s0[1], s0[3]), fmaxf(s1[1], s1[3]));
#pragma unroll
        for (int o = 4; o < 32; o <<= 1) {
            m0 = fmaxf(m0, __shfl_xor_sync(0xffffffffu, m0, o));
            m1 = fmaxf(m1, __shfl_xor_sync(0xffffffffu, m1, o));
        }
        if (lane < 2) *reinterpret_cast<float2*>(wmax + w * 4 + 2 * lane) = make_float2(m0, m1);
        bar_comp();
#pragma unroll
        for (int i = 0; i < 8; i++) {
            const float2 v = *reinterpret_cast<const float2*>(wmax + i * 4 + 2 * t1);
            m0 = fmaxf(m0, v.x); m1 = fmaxf(m1, v.y);
        }
        const float n0 = m0 * SC, n1 = m1 * SC;
        const uint32_t pa = pack_bf16(ex2(fmaf(th ? s1[0] : s0[0], SC, -n0)), ex2(fmaf(th ? s1[2] : s0[2], SC, -n0)));
        const uint32_t pb = pack_bf16(ex2(fmaf(th ? s1[1] : s0[1], SC, -n1)), ex2(fmaf(th ? s1[3] : s0[3], SC, -n1)));
        const uint32_t pd = sb + OFF_PS + t1 * (2 * 528) + (w * 32 + th * 16 + g) * 2;
        sts16(pd, pa); sts16(pd + 16, pa >> 16); sts16(pd + 528, pb); sts16(pd + 544, pb >> 16);
        float l0 = bf_lo(pa) + bf_hi(pa), l1 = bf_lo(pb) + bf_hi(pb);
#pragma unroll
        for (int o = 2; o < 32; o <<= 1) {
            l0 += __shfl_xor_sync(0xffffffffu, l0, o);
            l1 += __shfl_xor_sync(0xffffffffu, l1, o);
        }
        if (lane < 2) *reinterpret_cast<float2*>(wsum + w * 4 + 2 * lane) = make_float2(l0, l1);
        bar_comp();
    }
    PROF_T(6);

    const uint32_t a_off = (l8 + ((mi >> 1) << 3)) * 256 + (((2 * w + (mi & 1)) ^ l8) << 4);
    {
        const int hd = (lane >> 2) & 3;
        float l = 0.f, m = wmax[hd];
#pragma unroll
        for (int i = 0; i < 8; i++) { l += wsum[i * 4 + hd]; m = fmaxf(m, wmax[i * 4 + hd]); }
        m *= SC;
        const unsigned long long* lp = mail + MB_LX + ((cta & ~3) + t) * 16 + hd;
        if (tid < 16 && t == cq) ll_store(const_cast<unsigned long long*>(lp), __float_as_uint(m + lg2(l)), epoch);
        if (w >= 4) {
            const int b = w - 4, e = min(lane, 27), ge = hj * 28 + e;
            const unsigned long long* ap = mail + MB_AX + (ge >> 3) * 32 + b * 8 + (ge & 7);
            uint2 av[1] = {ll_load(ap)};
            ll_finish<1, 1, BACKOFF_NS>(av, ap, epoch);
            sts32(sb + OFF_AS + b * 144 + e * 4, av[0].x);
        }
        float o0[4] = {0.f, 0.f, 0.f, 0.f}, o1[4] = {0.f, 0.f, 0.f, 0.f};
        const uint32_t pb = sb + OFF_PS + (l8 & 3) * 528 + mi * 16;
        uint2 lv[1];
        float wgt;
#pragma unroll 1
        for (int ch = 0; ch < 4; ch++) {
            uint32_t pf0[4], pf1[4];
            ldsm4(pf0, pb + ch * 128);
            ldsm4(pf1, pb + ch * 128 + 64);
            if (ch == 2) lv[0] = ll_load(lp);
            if (ch == 3) {
                ll_finish<1, 1, BACKOFF_NS>(lv, lp, epoch);
                const float e = __uint_as_float(lv[0].x);
                float mx = fmaxf(e, __shfl_xor_sync(0xffffffffu, e, 1));
                mx = fmaxf(mx, __shfl_xor_sync(0xffffffffu, mx, 2));
                float den = ex2(e - mx);
                den += __shfl_xor_sync(0xffffffffu, den, 1);
                den += __shfl_xor_sync(0xffffffffu, den, 2);
                wgt = __shfl_sync(0xffffffffu, ex2(m - mx) * rcp(den), hb * 4);
            }
            mbar_wait(bar0 + 8 * (BAR_V0 + ch));
            PROF_T(14);
            mma_tile64(o0, o1, sb + OFF_V + ch * 16384 + a_off, pf0, pf1);
        }
        PROF_T(7);
        const float va = (th ? o0[1] + o1[1] : o0[0] + o1[0]) * wgt;
        const float vb = (th ? o0[3] + o1[3] : o0[2] + o1[2]) * wgt;
        ll_store(ox_slot, pack_bf16(va, vb), epoch);
    }
    PROF_T(8);

    {
        const unsigned long long* op = mail + MB_OX + (hj * 16 + (tid >> 6) * 4) * 64 + (tid & 63);
        uint2 ov[4];
        bar_comp();
        float bq[4] = {0.f, 0.f, 0.f, 0.f}, b2[4] = {0.f, 0.f, 0.f, 0.f};
        {
            uint32_t af0[4], af1[4], f0[4], f1[4], f2[4], f3[4];
            const uint32_t aa = sb + OFF_AS + (l8 & 3) * 144 + mi * 16;
            ldsm4(af0, aa);
            ldsm4(af1, aa + 64);
            mbar_wait(bar0 + 8 * BAR_W2);
            const uint32_t wb = sb + OFF_W2 + a_off;
            ldsm4t(f0, wb);
            ldsm4t(f1, wb + 16 * 256);
            ldsm4t(f2, wb + 32 * 256);
            ldsm4t(f3, wb + 48 * 256);
            mma16816(bq, f0, af0[0], af0[1]);
            mma16816(b2, f1, af0[2], af0[3]);
            mma16816(bq, f2, af1[0], af1[1]);
            mma1688(b2, f3[0], f3[1], af1[2]);
        }
        const float gt = rcp(1.f + ex2(-(gpart[2 * hb] + gpart[2 * hb + 1]) * LOG2E));
        const float rb = (1.f - gt) * (th ? bq[1] + b2[1] : bq[0] + b2[0]);
        const float rd = (1.f - gt) * (th ? bq[3] + b2[3] : bq[2] + b2[2]);
        PROF_T(11);
#pragma unroll
        for (int s = 0; s < 4; s++) ov[s] = ll_load(op + s * 64);
        ll_finish<4, 64, BACKOFF_NS>(ov, op, epoch);
        {
            const float v0 = (bf_lo(ov[0].x) + bf_lo(ov[1].x)) + (bf_lo(ov[2].x) + bf_lo(ov[3].x));
            const float v1 = (bf_hi(ov[0].x) + bf_hi(ov[1].x)) + (bf_hi(ov[2].x) + bf_hi(ov[3].x));
            const uint32_t pk = pack_bf16(v0, v1);
            const uint32_t od = sb + OFF_OS + (tid >> 6) * 272 + (tid & 56) * 4 + (tid & 7) * 2;
            sts16(od, pk); sts16(od + 16, pk >> 16);
        }
        bar_comp();
        PROF_T(9);
        uint32_t of[4][4];
        const uint32_t fb = sb + OFF_OS + (l8 & 3) * 272 + mi * 16;
#pragma unroll
        for (int i = 0; i < 4; i++) ldsm4(of[i], fb + i * 64);
        float a0[4] = {0.f, 0.f, 0.f, 0.f}, a1[4] = {0.f, 0.f, 0.f, 0.f};
        mbar_wait(bar0 + 8 * BAR_WO0);
        mma_tile64(a0, a1, sb + OFF_WO + a_off, of[0], of[1]);
        uint32_t f0[4], f1[4];
        mbar_wait(bar0 + 8 * BAR_WO1);
        ldsm4t(f0, sb + OFF_WO + 64 * 256 + a_off);
        ldsm4t(f1, sb + OFF_WO + 80 * 256 + a_off);
        mma16816(a0, f0, of[2][0], of[2][1]);
        mma16816(a1, f1, of[2][2], of[2][3]);
        mbar_wait(bar0 + 8 * BAR_WO2);
        PROF_T(10);
        ldsm4t(f0, sb + OFF_WO + 96 * 256 + a_off);
        ldsm4t(f1, sb + OFF_WO + 112 * 256 + a_off);
        mma16816(a0, f0, of[3][0], of[3][1]);
        mma16816(a1, f1, of[3][2], of[3][3]);
        ll_store(e4_slot,     __float_as_uint(fmaf(gt, th ? a0[1] + a1[1] : a0[0] + a1[0], rb)), epoch);
        ll_store(e4_slot + 8, __float_as_uint(fmaf(gt, th ? a0[3] + a1[3] : a0[2] + a1[2], rd)), epoch);
    }
    PROF_T(12);

    {
        uint2 v[2];
        {
            uint2 pa[NPOLL], pb[NPOLL];
#pragma unroll
            for (int i = 0; i < NPOLL; i++) {
                const uint32_t c0 = (uint32_t)clock();
                pa[i] = ll_load(ep);
                pb[i] = ll_load(ep + 32);
                if (i + 1 < NPOLL) while ((uint32_t)clock() - c0 < POLL_GAP) {}
            }
#pragma unroll 1
            for (int it = 0; it < SPIN_LIMIT; it++) {
                bool done = false;
#pragma unroll
                for (int i = 0; i < NPOLL; i++) {
                    if (!done) {
                        if (__all_sync(0xffffffffu, pa[i].y == epoch && pb[i].y == epoch)) { v[0] = pa[i]; v[1] = pb[i]; done = true; }
                        else { pa[i] = ll_load(ep); pb[i] = ll_load(ep + 32); }
                    }
                }
                if (done) break;
            }
        }
        PROF_T(15);
        float acc = __uint_as_float(v[0].x) + __uint_as_float(v[1].x);
        acc += __shfl_xor_sync(0xffffffffu, acc, 16);
        if (lane < 16) sts32(fin_st, __float_as_uint(acc));
        bar_comp();
        if (tid < 16) {
            float p[8];
#pragma unroll
            for (int i = 0; i < 8; i++) asm volatile("ld.shared.f32 %0, [%1];" : "=f"(p[i]) : "r"(fin_ld + i * 64) : "memory");
            *outp = __float2bfloat16(((p[0] + p[1]) + (p[2] + p[3])) + ((p[4] + p[5]) + (p[6] + p[7])));
            if (tid == 0) *(volatile unsigned int*)&mail[MB_EP + cta] = epoch;
        }
        PROF_T(13);
        if (tid == 0) PROF_DUMP(0, 16);
    }
}

}

extern "C" void kernel_launch(void* const* d_in, const int* in_sizes, int n_in, void* d_out, int out_size) {
    (void)in_sizes; (void)n_in; (void)out_size;
    const __nv_bfloat16* x  = (const __nv_bfloat16*)d_in[0];
    const __nv_bfloat16* kc = (const __nv_bfloat16*)d_in[1];
    const __nv_bfloat16* vc = (const __nv_bfloat16*)d_in[2];
    const __nv_bfloat16* wq = (const __nv_bfloat16*)d_in[3];
    const __nv_bfloat16* wo = (const __nv_bfloat16*)d_in[4];
    const __nv_bfloat16* w1 = (const __nv_bfloat16*)d_in[6];
    const __nv_bfloat16* b1 = (const __nv_bfloat16*)d_in[7];
    const __nv_bfloat16* w2 = (const __nv_bfloat16*)d_in[8];
    const __nv_bfloat16* gw = (const __nv_bfloat16*)d_in[9];
    cudaFuncSetAttribute(fused_decode_kernel, cudaFuncAttributeMaxDynamicSharedMemorySize, SMEM_BYTES);
    fused_decode_kernel<<<NCTA, NTHREADS, SMEM_BYTES, cudaStreamPerThread>>>(x, kc, vc, wq, wo, w1, b1, w2, gw,
                                                                            (__nv_bfloat16*)d_out);
}
```

```cpp
#include <cuda_runtime.h>
#include <cuda_bf16.h>
#include <stdint.h>

namespace {

constexpr int NCTA     = 128;
constexpr int NCOMP    = 256;
constexpr int NLOAD    = 128;
constexpr int NTHREADS = NCOMP + NLOAD;
#define WINDOW 8
#define TAU_TAIL TAU_NS
#define TAU_NS 85
#define T_K 1500
#define INIT_SLOTS 3
#define BACKOFF_NS 120
#define LOADER_FIRST 1
#define LOADER_INLINE __forceinline__
#define KV_INTERLEAVE 1
#define EVICT_FIRST 1
#define O_EARLY 0
#define Q_LATE 1
#define E4_FIRST 340
#define O_FIRST 400
#define LSE_CH 2
#define E4_GAP 0
#define BACKOFF_Q 200
constexpr int SPIN_LIMIT = 1 << 20;

constexpr int DM = 512, HQD = 4096, SK = 4096, WIN = 1024, FF = 1792;

constexpr int OFF_WQ   = 0;
constexpr int OFF_W1   = 32768;
constexpr int OFF_WO   = OFF_WQ;
constexpr int OFF_W2   = OFF_W1;
constexpr int OFF_K    = 49152;
constexpr int OFF_V    = OFF_K + 65536;
constexpr int OFF_XS   = OFF_V + 65536;
constexpr int OFF_PART = OFF_XS + 4 * 1040;
constexpr int OFF_QS   = OFF_PART + 6144;
constexpr int OFF_PS   = OFF_QS + 4 * 272;
constexpr int OFF_OS   = OFF_PS + 4 * 528;
constexpr int OFF_AS   = OFF_OS + 4 * 272;
constexpr int OFF_RED  = OFF_AS + 4 * 144;
constexpr int OFF_BAR  = OFF_RED + 320;
constexpr int SMEM_BYTES = OFF_BAR + 128;

enum { BAR_WQ = 0, BAR_K = 1, BAR_V0 = 2, BAR_W2 = 6, BAR_WO0 = 7, BAR_WO1 = 8, BAR_WO2 = 9, BAR_FREE = 10 };

constexpr int MB_QX = 0;
constexpr int MB_AX = MB_QX + 8 * 4 * 256;
constexpr int MB_LX = MB_AX + 112 * 32;
constexpr int MB_OX = MB_LX + NCTA * 16;
constexpr int MB_E4 = MB_OX + 32 * 16 * 64;
constexpr int MB_EP = MB_E4 + NCTA * 256;
constexpr int MB_WORDS = MB_EP + NCTA;
#define MAIL_PAD_WORDS 0
#define MAIL_OFF_WORDS 0
__device__ __align__(128) unsigned long long g_mail[MB_WORDS + MAIL_PAD_WORDS];
#define PROF_DECL
#define PROF_T(i) do {} while (0)
#define PROF_DUMP(base, n) do {} while (0)

__device__ __forceinline__ uint32_t smem_u32(const void* p) { return (uint32_t)__cvta_generic_to_shared(p); }
__device__ __forceinline__ void mbar_init(uint32_t bar, uint32_t cnt) {
    asm volatile("mbarrier.init.shared::cta.b64 [%0], %1;" ::"r"(bar), "r"(cnt) : "memory");
}
__device__ __forceinline__ void mbar_arrive(uint32_t bar) {
    asm volatile("mbarrier.arrive.shared::cta.b64 _, [%0];" ::"r"(bar) : "memory");
}
__device__ __forceinline__ void mbar_wait(uint32_t bar) {
    asm volatile("{\n.reg .pred p;\nW_%=:\nmbarrier.try_wait.parity.shared::cta.b64 p, [%0], 0;\n@!p bra W_%=;\n}" ::"r"(bar) : "memory");
}
__device__ __forceinline__ void cp_arrive(uint32_t bar) {
    asm volatile("cp.async.mbarrier.arrive.noinc.shared::cta.b64 [%0];" ::"r"(bar) : "memory");
}
template <int N, int SSTRIDE, int J = 0>
__device__ __forceinline__ void cp_steps(uint32_t dst, const char* src) {
    if constexpr (J < N) {
        asm volatile("{\n.reg .b64 pol;\ncreatepolicy.fractional.L2::evict_first.b64 pol, 1.0;\n"
                     "cp.async.cg.shared.global.L2::cache_hint [%0 + %2], [%1 + %3], 16, pol;\n}"
                     ::"r"(dst), "l"(src), "n"(J * 2048), "n"(J * SSTRIDE) : "memory");
        cp_steps<N, SSTRIDE, J + 1>(dst, src);
    }
}
template <int UNITS, int SSTRIDE>
__device__ __forceinline__ void burst(uint32_t dst, const char* src) {
#pragma unroll 1
    for (int i = 0; i < UNITS; i++) {
        cp_steps<4, SSTRIDE>(dst, src);
        dst += 4 * 2048;
        src += 4 * SSTRIDE;
    }
}
__device__ __forceinline__ uint32_t gtime32() { uint32_t t; asm volatile("mov.u32 %0, %%globaltimer_lo;" : "=r"(t)); return t; }
template <int N, int SSTRIDE, int TAU>
__device__ __forceinline__ void paced_unit(uint32_t t0, int& due, uint32_t dst, const char* src) {
    if (TAU > 0) {
        while ((int)(gtime32() - t0) < due) {}
        due += N * TAU;
    }
    cp_steps<N, SSTRIDE>(dst, src);
    asm volatile("cp.async.commit_group;\ncp.async.wait_group %0;" ::"n"(WINDOW - 1) : "memory");
}
template <int UNITS, int SSTRIDE, int USTRIDE, int TAU>
__device__ __forceinline__ void stream(uint32_t t0, int& due, uint32_t dst, const char* src) {
#pragma unroll 1
    for (int i = 0; i < UNITS; i++) {
        paced_unit<4, SSTRIDE, TAU>(t0, due, dst, src);
        dst += 4 * 2048;
        src += USTRIDE;
    }
}
__device__ __forceinline__ void bar_comp() { asm volatile("bar.sync 1, 256;" ::: "memory"); }

__device__ __forceinline__ void ldsm4(uint32_t (&r)[4], uint32_t a) {
    asm volatile("ldmatrix.sync.aligned.m8n8.x4.shared.b16 {%0,%1,%2,%3}, [%4];"
                 : "=r"(r[0]), "=r"(r[1]), "=r"(r[2]), "=r"(r[3]) : "r"(a) : "memory");
}
__device__ __forceinline__ void ldsm4t(uint32_t (&r)[4], uint32_t a) {
    asm volatile("ldmatrix.sync.aligned.m8n8.x4.trans.shared.b16 {%0,%1,%2,%3}, [%4];"
                 : "=r"(r[0]), "=r"(r[1]), "=r"(r[2]), "=r"(r[3]) : "r"(a) : "memory");
}
__device__ __forceinline__ void mma16816(float (&c)[4], const uint32_t (&a)[4], uint32_t b0, uint32_t b1) {
    asm volatile("mma.sync.aligned.m16n8k16.row.col.f32.bf16.bf16.f32 {%0,%1,%2,%3}, {%4,%5,%6,%7}, {%8,%9}, {%0,%1,%2,%3};"
                 : "+f"(c[0]), "+f"(c[1]), "+f"(c[2]), "+f"(c[3])
                 : "r"(a[0]), "r"(a[1]), "r"(a[2]), "r"(a[3]), "r"(b0), "r"(b1));
}
__device__ __forceinline__ void mma1688(float (&c)[4], uint32_t a0, uint32_t a1, uint32_t b0) {
    asm volatile("mma.sync.aligned.m16n8k8.row.col.f32.bf16.bf16.f32 {%0,%1,%2,%3}, {%4,%5}, {%6}, {%0,%1,%2,%3};"
                 : "+f"(c[0]), "+f"(c[1]), "+f"(c[2]), "+f"(c[3])
                 : "r"(a0), "r"(a1), "r"(b0));
}
__device__ __forceinline__ void mma_tile64(float (&c0)[4], float (&c1)[4], uint32_t a, const uint32_t (&b0)[4], const uint32_t (&b1)[4]) {
    uint32_t f0[4], f1[4], f2[4], f3[4];
    ldsm4t(f0, a);
    ldsm4t(f1, a + 16 * 256);
    ldsm4t(f2, a + 32 * 256);
    ldsm4t(f3, a + 48 * 256);
    mma16816(c0, f0, b0[0], b0[1]);
    mma16816(c1, f1, b0[2], b0[3]);
    mma16816(c0, f2, b1[0], b1[1]);
    mma16816(c1, f3, b1[2], b1[3]);
}
__device__ __forceinline__ uint32_t pack_bf16(float lo, float hi) {
    uint32_t r;
    asm("cvt.rn.bf16x2.f32 %0, %1, %2;" : "=r"(r) : "f"(hi), "f"(lo));
    return r;
}
__device__ __forceinline__ float bf_lo(uint32_t v) { return __uint_as_float(v << 16); }
__device__ __forceinline__ float bf_hi(uint32_t v) { return __uint_as_float(v & 0xffff0000u); }
__device__ __forceinline__ float ex2(float x) { float y; asm("ex2.approx.ftz.f32 %0, %1;" : "=f"(y) : "f"(x)); return y; }
__device__ __forceinline__ float lg2(float x) { float y; asm("lg2.approx.ftz.f32 %0, %1;" : "=f"(y) : "f"(x)); return y; }
__device__ __forceinline__ float rcp(float x) { float y; asm("rcp.approx.ftz.f32 %0, %1;" : "=f"(y) : "f"(x)); return y; }
__device__ __forceinline__ float dot2(uint32_t a, uint32_t b, float acc) {
    return fmaf(bf_hi(a), bf_hi(b), fmaf(bf_lo(a), bf_lo(b), acc));
}
__device__ __forceinline__ void sts32(uint32_t a, uint32_t v) { asm volatile("st.shared.b32 [%0], %1;" ::"r"(a), "r"(v) : "memory"); }
__device__ __forceinline__ void sts16(uint32_t a, uint32_t v) { asm volatile("st.shared.b16 [%0], %1;" ::"r"(a), "h"((unsigned short)v) : "memory"); }

__device__ __forceinline__ void ll_store(unsigned long long* p, uint32_t payload, uint32_t epoch) {
    asm volatile("{\n.reg .b64 v;\nmov.b64 v, {%1, %2};\nst.relaxed.gpu.global.b64 [%0], v;\n}" ::"l"(p), "r"(payload), "r"(epoch) : "memory");
}
__device__ __forceinline__ uint2 ll_load(const unsigned long long* p) {
    uint2 v;
    asm volatile("{\n.reg .b64 v;\nld.relaxed.gpu.global.b64 v, [%2];\nmov.b64 {%0, %1}, v;\n}" : "=r"(v.x), "=r"(v.y) : "l"(p) : "memory");
    return v;
}
template <int N, int STRIDE, int SLEEP>
__device__ __forceinline__ void ll_finish(uint2 (&v)[N], const unsigned long long* p, uint32_t epoch) {
#pragma unroll 1
    for (int it = 0; it < SPIN_LIMIT; it++) {
        bool ok = true;
#pragma unroll
        for (int i = 0; i < N; i++) ok = ok && v[i].y == epoch;
        if (__all_sync(0xffffffffu, ok)) break;
        if (SLEEP) __nanosleep(SLEEP);
#pragma unroll
        for (int i = 0; i < N; i++)
            if (v[i].y != epoch) v[i] = ll_load(p + i * STRIDE);
    }
}

constexpr float LOG2E = 1.4426950408889634f;
__device__ __forceinline__ float mish(float h) {
    const float e = ex2(-fabsf(h) * LOG2E);
    const float num = h >= 0.f ? fmaf(2.f, e, 1.f) : e * (e + 2.f);
    const float den = num + (h >= 0.f ? 2.f * e * e : 2.f);
    return h * num * rcp(den);
}

__device__ LOADER_INLINE void loader(const __nv_bfloat16* __restrict__ kc, const __nv_bfloat16* __restrict__ vc,
                                    const __nv_bfloat16* __restrict__ wq, const __nv_bfloat16* __restrict__ wo,
                                    const __nv_bfloat16* __restrict__ w1, const __nv_bfloat16* __restrict__ w2, uint32_t sb) {
    const int cta = blockIdx.x;
    const int kvh = cta >> 4, r = cta & 15;
    const int hj = cta >> 2, cq = cta & 3;
    const uint32_t bar0 = sb + OFF_BAR;
    {
        const int lt = LOADER_FIRST ? threadIdx.x : threadIdx.x - NCOMP;
        PROF_DECL;
        PROF_T(16);
        const uint32_t t0 = gtime32();
        burst<4, 32 * HQD * 2>(sb + OFF_WQ + (lt >> 2) * 64 + (((lt & 3) ^ ((lt >> 3) & 3)) << 4),
                               (const char*)wq + (size_t)(lt >> 2) * (HQD * 2) + cta * 64 + (lt & 3) * 16);
        if (cta < 112)
            burst<2, 64 * FF * 2>(sb + OFF_W1 + (lt >> 1) * 32 + (((lt & 1) ^ ((lt >> 3) & 1)) << 4),
                                  (const char*)w1 + (size_t)(lt >> 1) * (FF * 2) + cta * 32 + (lt & 1) * 16);
        asm volatile("cp.async.commit_group;" ::: "memory");
        if (lt <= BAR_FREE) mbar_init(bar0 + 8 * lt, lt == BAR_FREE ? 8 : NLOAD);
        asm volatile("bar.sync 2, 128;\nbar.arrive 0, 384;" ::: "memory");
        const int row = lt >> 4, c = lt & 15;
        const uint32_t sw = sb + row * 256 + ((c ^ row) << 4);
        constexpr int KVU = KV_INTERLEAVE ? 4 * 8192 : 8192;
        const size_t kvoff = ((size_t)((r >> 2) * 8 + kvh) * SK + (SK - WIN)) * 256 + (r & 3) * (KV_INTERLEAVE ? 8192 : 65536) + lt * 16;
        int due = T_K;
        cp_arrive(bar0 + 8 * BAR_WQ);
        {
            uint32_t dst = sw + OFF_K;
            const char* src = (const char*)kc + kvoff;
#pragma unroll 1
            for (int u = 0; u < 16; u++) {
                paced_unit<4, 2048, TAU_NS>(t0, due, dst, src);
                dst += 8192;
                src = u == 7 ? (const char*)vc + kvoff : src + KVU;
                if (u >= 7 && (u & 1)) cp_arrive(bar0 + 8 * (BAR_K + ((u - 7) >> 1)));
            }
        }
        PROF_T(18);
        mbar_wait(bar0 + 8 * BAR_FREE);
        const int wofs = row * (DM * 2) + cq * 256 + c * 16;
        {
            const char* src = (const char*)w2 + hj * (56 * DM * 2) + wofs;
            paced_unit<4, 8 * DM * 2, TAU_TAIL>(t0, due, sw + OFF_W2, src);
            paced_unit<3, 8 * DM * 2, TAU_TAIL>(t0, due, sw + OFF_W2 + 4 * 2048, src + 4 * 8 * DM * 2);
            cp_arrive(bar0 + 8 * BAR_W2);
        }
        {
            const char* src = (const char*)wo + hj * (128 * DM * 2) + wofs;
#pragma unroll 1
            for (int u = 0; u < 4; u++) {
                paced_unit<4, 8 * DM * 2, TAU_TAIL>(t0, due, sw + OFF_WO + u * 8192, src + u * (32 * DM * 2));
                if (u >= 1) cp_arrive(bar0 + 8 * (BAR_WO0 + u - 1));
            }
        }
        PROF_T(19);
        asm volatile("cp.async.wait_all;" ::: "memory");
        PROF_T(20);
        if (lt == 0) PROF_DUMP(16, 5);
    }
}

__global__ void __launch_bounds__(NTHREADS, 1)
fused_decode_kernel(const __nv_bfloat16* __restrict__ x, const __nv_bfloat16* __restrict__ kc,
                    const __nv_bfloat16* __restrict__ vc, const __nv_bfloat16* __restrict__ wq,
                    const __nv_bfloat16* __restrict__ wo, const __nv_bfloat16* __restrict__ w1,
                    const __nv_bfloat16* __restrict__ b1, const __nv_bfloat16* __restrict__ w2,
                    const __nv_bfloat16* __restrict__ gw, __nv_bfloat16* __restrict__ out) {
    extern __shared__ __align__(128) unsigned char smem[];
    const uint32_t sb = smem_u32(smem);
    const int cta = blockIdx.x;
    const int kvh = cta >> 4, r = cta & 15;
    const int hj = cta >> 2, cq = cta & 3;
    const uint32_t bar0 = sb + OFF_BAR;

    if (LOADER_FIRST ? threadIdx.x < NLOAD : threadIdx.x >= NCOMP) {
        loader(kc, vc, wq, wo, w1, w2, sb);
        return;
    }

    const int tid = LOADER_FIRST ? threadIdx.x - NLOAD : threadIdx.x;
    const int lane = tid & 31, w = tid >> 5;
    const int g = lane >> 2, t = lane & 3;
    const int t1 = t & 1, th = t >> 1;
    const int mi = lane >> 3, l8 = lane & 7;
    const int ab = r >> 2;
    PROF_DECL;
    PROF_T(0);
    float* const part = reinterpret_cast<float*>(smem + OFF_PART);
    float* const wmax = reinterpret_cast<float*>(smem + OFF_RED);
    float* const wsum = wmax + 32;
    float* const gpart = wmax + 64;
    unsigned long long* const mail = g_mail + MAIL_OFF_WORDS;

    const uint4 xv = __ldg(reinterpret_cast<const uint4*>(x) + tid);
    const uint4 gv = __ldg(reinterpret_cast<const uint4*>(gw) + (tid & 63));
    const uint32_t epoch = *(volatile unsigned int*)&mail[MB_EP + cta] + 1u;
    const uint32_t b1v = __ldg(reinterpret_cast<const uint32_t*>(b1 + (cta < 112 ? cta : 0) * 16) + (tid & 7));
    const uint32_t tag16 = epoch % 65535u + 1u;
    const int hb = 2 * t1 + th;
    unsigned long long* const ox_slot = mail + MB_OX + ((kvh * 4 + hb) * 16 + r) * 64 + w * 8 + g;
    unsigned long long* e4_slot = mail + MB_E4 + ((cq * 8 + w) * 32 + hj) * 32 + hb * 8 + g;
    const unsigned long long* ep = mail + MB_E4 + ((cq * 8 + (hj & 7)) * 32 + w * 4 + (lane >> 3)) * 32 + (hj >> 3) * 8 + (lane & 7);
    __nv_bfloat16* outp = out + (hj >> 3) * DM + cq * 128 + (hj & 7) * 16 + (tid & 15);
    uint32_t fin_st = sb + OFF_PART + (w * 16 + (lane & 7)) * 4, fin_ld = sb + OFF_PART + (tid & 15) * 4;
    asm volatile("" : "+l"(e4_slot), "+l"(ep), "+l"(outp), "+r"(fin_st), "+r"(fin_ld));
    *reinterpret_cast<uint4*>(smem + OFF_XS + (tid >> 6) * 1040 + (tid & 63) * 16) = xv;
    {
        float acc = dot2(xv.w, gv.w, dot2(xv.z, gv.z, dot2(xv.y, gv.y, dot2(xv.x, gv.x, 0.f))));
#pragma unroll
        for (int o = 16; o > 0; o >>= 1) acc += __shfl_xor_sync(0xffffffffu, acc, o);
        if (lane == 0) gpart[w] = acc;
    }
    asm volatile("bar.sync 0, 384;" ::: "memory");
    PROF_T(1);
    if (INIT_SLOTS & 2) ll_store(ox_slot, 0u, 0u);
    if ((INIT_SLOTS & 4) && tid < 16 && t == cq) ll_store(mail + MB_LX + cta * 16 + g, 0u, 0u);
    if (INIT_SLOTS & 1) ll_store(e4_slot, 0u, 0u);

    {
        uint32_t xb[2][4];
        const uint32_t xa = sb + OFF_XS + (l8 & 3) * 1040 + (w * 64 + mi * 8) * 2;
        ldsm4(xb[0], xa);
        ldsm4(xb[1], xa + 64);
        const int kr = w * 64 + l8 + ((mi >> 1) << 3);
        const uint32_t aq0 = sb + OFF_WQ + kr * 64 + (((mi & 1) ^ ((kr >> 1) & 3)) << 4);
        const uint32_t aq1 = aq0 ^ 32;
        const uint32_t ah = sb + OFF_W1 + kr * 32 + (((mi & 1) ^ ((kr >> 2) & 1)) << 4);
        float cq0[4] = {0.f, 0.f, 0.f, 0.f}, cq1[4] = {0.f, 0.f, 0.f, 0.f}, ch[4] = {0.f, 0.f, 0.f, 0.f};
        mbar_wait(bar0 + 8 * BAR_WQ);
        PROF_T(2);
#pragma unroll
        for (int ks = 0; ks < 4; ks++) {
            uint32_t a0[4], a1[4], a2[4];
            ldsm4t(a0, aq0 + ks * 1024);
            ldsm4t(a1, aq1 + ks * 1024);
            ldsm4t(a2, ah + ks * 512);
            const uint32_t bb0 = xb[ks >> 1][(ks & 1) * 2], bb1 = xb[ks >> 1][(ks & 1) * 2 + 1];
            mma16816(cq0, a0, bb0, bb1);
            mma16816(cq1, a1, bb0, bb1);
            mma16816(ch, a2, bb0, bb1);
        }
        __syncwarp();
        if (lane == 0) mbar_arrive(bar0 + 8 * BAR_FREE);
        if (t < 2) {
            float* p0 = part + (w * 4 + 2 * t) * 48 + g;
            p0[0] = cq0[0]; p0[48] = cq0[1]; p0[8] = cq0[2]; p0[56] = cq0[3];
            p0[16] = cq1[0]; p0[64] = cq1[1]; p0[24] = cq1[2]; p0[72] = cq1[3];
            p0[32] = ch[0]; p0[80] = ch[1]; p0[40] = ch[2]; p0[88] = ch[3];
        }
        bar_comp();
        if (tid < 96) {
            const bool isq = tid < 64;
            const int b = isq ? tid >> 4 : (tid - 64) >> 3;
            const int cp = isq ? tid & 15 : 16 + (tid & 7);
            float v0 = 0.f, v1 = 0.f;
#pragma unroll
            for (int i = 0; i < 8; i++) {
                const float2 v = *reinterpret_cast<const float2*>(part + (i * 4 + b) * 48 + 2 * cp);
                v0 += v.x; v1 += v.y;
            }
            if (!isq) { v0 = mish(v0 + bf_lo(b1v)); v1 = mish(v1 + bf_hi(b1v)); }
            const int slot = isq ? MB_QX + (kvh * 4 + b) * 256 + r * 16 + cp : MB_AX + cta * 32 + (tid - 64);
            if (isq || cta < 112) ll_store(mail + slot, pack_bf16(v0, v1), epoch);
        }
    }
    PROF_T(3);

    mbar_wait(bar0 + 8 * BAR_K);
    {
        const unsigned long long* qp = mail + MB_QX + (kvh * 4 + ab) * 256 + tid;
        uint2 v[1] = {ll_load(qp)};
        ll_finish<1, 1, BACKOFF_Q>(v, qp, epoch);
        sts32(sb + OFF_QS + (tid >> 6) * 272 + (tid & 63) * 4, v[0].x);
    }
    bar_comp();
    PROF_T(5);

    constexpr float SC = 0.08838834764831845f * LOG2E;
    {
        float s0[4] = {0.f, 0.f, 0.f, 0.f}, s1[4] = {0.f, 0.f, 0.f, 0.f};
        const uint32_t qa = sb + OFF_QS + (l8 & 3) * 272 + mi * 16;
        const uint32_t kb = sb + OFF_K + (w * 32 + (lane & 15)) * 256;
        const int kx = (lane >> 4) ^ l8;
        mbar_wait(bar0 + 8 * BAR_K);
        PROF_T(4);
#pragma unroll 1
        for (int i = 0; i < 4; i++) {
            uint32_t qb[4], a0[4], a1[4], a2[4], a3[4];
            const uint32_t o0 = (uint32_t)((kx ^ (4 * i)) << 4), o1 = o0 ^ 32;
            ldsm4(qb, qa + i * 64);
            ldsm4(a0, kb + o0);
            ldsm4(a1, kb + 16 * 256 + o0);
            ldsm4(a2, kb + o1);
            ldsm4(a3, kb + 16 * 256 + o1);
            mma16816(s0, a0, qb[0], qb[1]);
            mma16816(s1, a1, qb[0], qb[1]);
            mma16816(s0, a2, qb[2], qb[3]);
            mma16816(s1, a3, qb[2], qb[3]);
        }
        float m0 = fmaxf(fmaxf(s0[0], s0[2]), fmaxf(s1[0], s1[2]));
        float m1 = fmaxf(fmaxf(s0[1], s0[3]), fmaxf(s1[1], s1[3]));
#pragma unroll
        for (int o = 4; o < 32; o <<= 1) {
            m0 = fmaxf(m0, __shfl_xor_sync(0xffffffffu, m0, o));
            m1 = fmaxf(m1, __shfl_xor_sync(0xffffffffu, m1, o));
        }
        if (lane < 2) *reinterpret_cast<float2*>(wmax + w * 4 + 2 * lane) = make_float2(m0, m1);
        bar_comp();
#pragma unroll
        for (int i = 0; i < 8; i++) {
            const float2 v = *reinterpret_cast<const float2*>(wmax + i * 4 + 2 * t1);
            m0 = fmaxf(m0, v.x); m1 = fmaxf(m1, v.y);
        }
        const float n0 = m0 * SC, n1 = m1 * SC;
        const uint32_t pa = pack_bf16(ex2(fmaf(th ? s1[0] : s0[0], SC, -n0)), ex2(fmaf(th ? s1[2] : s0[2], SC, -n0)));
        const uint32_t pb = pack_bf16(ex2(fmaf(th ? s1[1] : s0[1], SC, -n1)), ex2(fmaf(th ? s1[3] : s0[3], SC, -n1)));
        const uint32_t pd = sb + OFF_PS + t1 * (2 * 528) + (w * 32 + th * 16 + g) * 2;
        sts16(pd, pa); sts16(pd + 16, pa >> 16); sts16(pd + 528, pb); sts16(pd + 544, pb >> 16);
        float l0 = bf_lo(pa) + bf_hi(pa), l1 = bf_lo(pb) + bf_hi(pb);
#pragma unroll
        for (int o = 2; o < 32; o <<= 1) {
            l0 += __shfl_xor_sync(0xffffffffu, l0, o);
            l1 += __shfl_xor_sync(0xffffffffu, l1, o);
        }
        if (lane < 2) *reinterpret_cast<float2*>(wsum + w * 4 + 2 * lane) = make_float2(l0, l1);
        bar_comp();
    }
    PROF_T(6);

    const uint32_t a_off = (l8 + ((mi >> 1) << 3)) * 256 + (((2 * w + (mi & 1)) ^ l8) << 4);
    {
        const int hd = (lane >> 2) & 3;
        float l = 0.f, m = wmax[hd];
#pragma unroll
        for (int i = 0; i < 8; i++) { l += wsum[i * 4 + hd]; m = fmaxf(m, wmax[i * 4 + hd]); }
        m *= SC;
        const unsigned long long* lp = mail + MB_LX + ((cta & ~3) + t) * 16 + hd;
        if (tid < 16 && t == cq) ll_store(const_cast<unsigned long long*>(lp), __float_as_uint(m + lg2(l)), epoch);
        if (w >= 4) {
            const int b = w - 4, e = min(lane, 27), ge = hj * 28 + e;
            const unsigned long long* ap = mail + MB_AX + (ge >> 3) * 32 + b * 8 + (ge & 7);
            uint2 av[1] = {ll_load(ap)};
            ll_finish<1, 1, BACKOFF_NS>(av, ap, epoch);
            sts32(sb + OFF_AS + b * 144 + e * 4, av[0].x);
        }
        float o0[4] = {0.f, 0.f, 0.f, 0.f}, o1[4] = {0.f, 0.f, 0.f, 0.f};
        const uint32_t pb = sb + OFF_PS + (l8 & 3) * 528 + mi * 16;
        uint2 lv[1];
        float wgt;
#pragma unroll 1
        for (int ch = 0; ch < 4; ch++) {
            uint32_t pf0[4], pf1[4];
            ldsm4(pf0, pb + ch * 128);
            ldsm4(pf1, pb + ch * 128 + 64);
            if (ch == LSE_CH) lv[0] = ll_load(lp);
            if (ch == 3) {
                ll_finish<1, 1, BACKOFF_NS>(lv, lp, epoch);
                const float e = __uint_as_float(lv[0].x);
                float mx = fmaxf(e, __shfl_xor_sync(0xffffffffu, e, 1));
                mx = fmaxf(mx, __shfl_xor_sync(0xffffffffu, mx, 2));
                float den = ex2(e - mx);
                den += __shfl_xor_sync(0xffffffffu, den, 1);
                den += __shfl_xor_sync(0xffffffffu, den, 2);
                wgt = __shfl_sync(0xffffffffu, ex2(m - mx) * rcp(den), hb * 4);
            }
            mbar_wait(bar0 + 8 * (BAR_V0 + ch));
            PROF_T(14);
            mma_tile64(o0, o1, sb + OFF_V + ch * 16384 + a_off, pf0, pf1);
        }
        PROF_T(7);
        const float va = (th ? o0[1] + o1[1] : o0[0] + o1[0]) * wgt;
        const float vb = (th ? o0[3] + o1[3] : o0[2] + o1[2]) * wgt;
        ll_store(ox_slot, pack_bf16(va, vb), epoch);
    }
    PROF_T(8);

    {
        const unsigned long long* op = mail + MB_OX + (hj * 16 + (tid >> 6) * 4) * 64 + (tid & 63);
        uint2 ov[4];
        bar_comp();
        float bq[4] = {0.f, 0.f, 0.f, 0.f}, b2[4] = {0.f, 0.f, 0.f, 0.f};
        {
            uint32_t af0[4], af1[4], f0[4], f1[4], f2[4], f3[4];
            const uint32_t aa = sb + OFF_AS + (l8 & 3) * 144 + mi * 16;
            ldsm4(af0, aa);
            ldsm4(af1, aa + 64);
            mbar_wait(bar0 + 8 * BAR_W2);
            const uint32_t wb = sb + OFF_W2 + a_off;
            ldsm4t(f0, wb);
            ldsm4t(f1, wb + 16 * 256);
            ldsm4t(f2, wb + 32 * 256);
            ldsm4t(f3, wb + 48 * 256);
            mma16816(bq, f0, af0[0], af0[1]);
            mma16816(b2, f1, af0[2], af0[3]);
            mma16816(bq, f2, af1[0], af1[1]);
            mma1688(b2, f3[0], f3[1], af1[2]);
        }
        const float gt = rcp(1.f + ex2(-(gpart[2 * hb] + gpart[2 * hb + 1]) * LOG2E));
        const float rb = (1.f - gt) * (th ? bq[1] + b2[1] : bq[0] + b2[0]);
        const float rd = (1.f - gt) * (th ? bq[3] + b2[3] : bq[2] + b2[2]);
        PROF_T(11);
        if (O_FIRST) { const uint32_t c0 = (uint32_t)clock(); while ((uint32_t)clock() - c0 < O_FIRST) {} }
#pragma unroll
        for (int s = 0; s < 4; s++) ov[s] = ll_load(op + s * 64);
        ll_finish<4, 64, BACKOFF_NS>(ov, op, epoch);
        {
            const float v0 = (bf_lo(ov[0].x) + bf_lo(ov[1].x)) + (bf_lo(ov[2].x) + bf_lo(ov[3].x));
            const float v1 = (bf_hi(ov[0].x) + bf_hi(ov[1].x)) + (bf_hi(ov[2].x) + bf_hi(ov[3].x));
            const uint32_t pk = pack_bf16(v0, v1);
            const uint32_t od = sb + OFF_OS + (tid >> 6) * 272 + (tid & 56) * 4 + (tid & 7) * 2;
            sts16(od, pk); sts16(od + 16, pk >> 16);
        }
        bar_comp();
        PROF_T(9);
        uint32_t of[4][4];
        const uint32_t fb = sb + OFF_OS + (l8 & 3) * 272 + mi * 16;
#pragma unroll
        for (int i = 0; i < 4; i++) ldsm4(of[i], fb + i * 64);
        float a0[4] = {0.f, 0.f, 0.f, 0.f}, a1[4] = {0.f, 0.f, 0.f, 0.f};
        mbar_wait(bar0 + 8 * BAR_WO0);
        mma_tile64(a0, a1, sb + OFF_WO + a_off, of[0], of[1]);
        uint32_t f0[4], f1[4];
        mbar_wait(bar0 + 8 * BAR_WO1);
        ldsm4t(f0, sb + OFF_WO + 64 * 256 + a_off);
        ldsm4t(f1, sb + OFF_WO + 80 * 256 + a_off);
        mma16816(a0, f0, of[2][0], of[2][1]);
        mma16816(a1, f1, of[2][2], of[2][3]);
        mbar_wait(bar0 + 8 * BAR_WO2);
        PROF_T(10);
        ldsm4t(f0, sb + OFF_WO + 96 * 256 + a_off);
        ldsm4t(f1, sb + OFF_WO + 112 * 256 + a_off);
        mma16816(a0, f0, of[3][0], of[3][1]);
        mma16816(a1, f1, of[3][2], of[3][3]);
        const uint32_t r0 = __float_as_uint(fmaf(gt, th ? a0[1] + a1[1] : a0[0] + a1[0], rb)) + 0x80u;
        const uint32_t r1 = __float_as_uint(fmaf(gt, th ? a0[3] + a1[3] : a0[2] + a1[2], rd)) + 0x80u;
        ll_store(e4_slot, ((r1 << 8) & 0xffff0000u) | tag16, (r0 & 0xffffff00u) | (r1 >> 24));
    }
    PROF_T(12);

    {
        uint2 v;
        {
            if (E4_FIRST) { const uint32_t c0 = (uint32_t)clock(); while ((uint32_t)clock() - c0 < E4_FIRST) {} }
            v = ll_load(ep);
#pragma unroll 1
            for (int it = 0; it < SPIN_LIMIT; it++) {
                if (__all_sync(0xffffffffu, (v.x & 0xffffu) == tag16)) break;
                if (E4_GAP) { const uint32_t c0 = (uint32_t)clock(); while ((uint32_t)clock() - c0 < E4_GAP) {} }
                if ((v.x & 0xffffu) != tag16) v = ll_load(ep);
            }
        }
        PROF_T(15);
        float s0 = __uint_as_float(v.y & 0xffffff00u), s1 = __uint_as_float((v.y << 24) | ((v.x & 0xffff0000u) >> 8));
        s0 += __shfl_xor_sync(0xffffffffu, s0, 8);
        s1 += __shfl_xor_sync(0xffffffffu, s1, 8);
        s0 += __shfl_xor_sync(0xffffffffu, s0, 16);
        s1 += __shfl_xor_sync(0xffffffffu, s1, 16);
        if (lane < 8) { sts32(fin_st, __float_as_uint(s0)); sts32(fin_st + 32, __float_as_uint(s1)); }
        bar_comp();
        if (tid < 16) {
            float p[8];
#pragma unroll
            for (int i = 0; i < 8; i++) asm volatile("ld.shared.f32 %0, [%1];" : "=f"(p[i]) : "r"(fin_ld + i * 64) : "memory");
            *outp = __float2bfloat16(((p[0] + p[1]) + (p[2] + p[3])) + ((p[4] + p[5]) + (p[6] + p[7])));
            if (tid == 0) *(volatile unsigned int*)&mail[MB_EP + cta] = epoch;
        }
        PROF_T(13);
        if (tid == 0) PROF_DUMP(0, 16);
    }
}

}

extern "C" void kernel_launch(void* const* d_in, const int* in_sizes, int n_in, void* d_out, int out_size) {
    (void)in_sizes; (void)n_in; (void)out_size;
    const __nv_bfloat16* x  = (const __nv_bfloat16*)d_in[0];
    const __nv_bfloat16* kc = (const __nv_bfloat16*)d_in[1];
    const __nv_bfloat16* vc = (const __nv_bfloat16*)d_in[2];
    const __nv_bfloat16* wq = (const __nv_bfloat16*)d_in[3];
    const __nv_bfloat16* wo = (const __nv_bfloat16*)d_in[4];
    const __nv_bfloat16* w1 = (const __nv_bfloat16*)d_in[6];
    const __nv_bfloat16* b1 = (const __nv_bfloat16*)d_in[7];
    const __nv_bfloat16* w2 = (const __nv_bfloat16*)d_in[8];
    const __nv_bfloat16* gw = (const __nv_bfloat16*)d_in[9];
    cudaFuncSetAttribute(fused_decode_kernel, cudaFuncAttributeMaxDynamicSharedMemorySize, SMEM_BYTES);
    fused_decode_kernel<<<NCTA, NTHREADS, SMEM_BYTES, cudaStreamPerThread>>>(x, kc, vc, wq, wo, w1, b1, w2, gw,
                                                                            (__nv_bfloat16*)d_out);
}
```

```cpp
#include <cuda_runtime.h>
#include <cuda_bf16.h>
#include <stdint.h>

namespace {

constexpr int NCTA     = 128;
constexpr int NCOMP    = 256;
constexpr int NLOAD    = 128;
constexpr int NTHREADS = NCOMP + NLOAD;

constexpr int WINDOW   = 8;
constexpr int TAU_NS   = 85;
constexpr int T_K      = 1500;
constexpr int BACKOFF_NS = 120;
constexpr int O_FIRST    = 400;
constexpr int E4_FIRST   = 340;
constexpr int SPIN_LIMIT = 1 << 20;

constexpr int DM = 512, HQD = 4096, SK = 4096, WIN = 1024, FF = 1792;

constexpr int OFF_WQ   = 0;
constexpr int OFF_W1   = 32768;
constexpr int OFF_WO   = OFF_WQ;
constexpr int OFF_W2   = OFF_W1;
constexpr int OFF_K    = 49152;
constexpr int OFF_V    = OFF_K + 65536;
constexpr int OFF_XS   = OFF_V + 65536;
constexpr int OFF_PART = OFF_XS + 4 * 1040;
constexpr int OFF_QS   = OFF_PART + 6144;
constexpr int OFF_PS   = OFF_QS + 4 * 272;
constexpr int OFF_OS   = OFF_PS + 4 * 528;
constexpr int OFF_AS   = OFF_OS + 4 * 272;
constexpr int OFF_RED  = OFF_AS + 4 * 144;
constexpr int OFF_BAR  = OFF_RED + 320;
constexpr int SMEM_BYTES = OFF_BAR + 128;

enum { BAR_WQ = 0, BAR_K = 1, BAR_V0 = 2, BAR_W2 = 6, BAR_WO0 = 7, BAR_WO1 = 8, BAR_WO2 = 9, BAR_FREE = 10 };

constexpr int MB_QX = 0;
constexpr int MB_AX = MB_QX + 8 * 4 * 256;
constexpr int MB_LX = MB_AX + 112 * 32;
constexpr int MB_OX = MB_LX + NCTA * 16;
constexpr int MB_E4 = MB_OX + 32 * 16 * 64;
constexpr int MB_EP = MB_E4 + NCTA * 256;
constexpr int MB_WORDS = MB_EP + NCTA;
__device__ __align__(128) unsigned long long g_mail[MB_WORDS];

__device__ __forceinline__ uint32_t smem_u32(const void* p) { return (uint32_t)__cvta_generic_to_shared(p); }
__device__ __forceinline__ void mbar_init(uint32_t bar, uint32_t cnt) {
    asm volatile("mbarrier.init.shared::cta.b64 [%0], %1;" ::"r"(bar), "r"(cnt) : "memory");
}
__device__ __forceinline__ void mbar_arrive(uint32_t bar) {
    asm volatile("mbarrier.arrive.shared::cta.b64 _, [%0];" ::"r"(bar) : "memory");
}
__device__ __forceinline__ void mbar_wait(uint32_t bar) {
    asm volatile("{\n.reg .pred p;\nW_%=:\nmbarrier.try_wait.parity.shared::cta.b64 p, [%0], 0;\n@!p bra W_%=;\n}" ::"r"(bar) : "memory");
}
__device__ __forceinline__ void cp_arrive(uint32_t bar) {
    asm volatile("cp.async.mbarrier.arrive.noinc.shared::cta.b64 [%0];" ::"r"(bar) : "memory");
}
template <int N, int SSTRIDE, int J = 0>
__device__ __forceinline__ void cp_steps(uint32_t dst, const char* src) {
    if constexpr (J < N) {
        asm volatile("{\n.reg .b64 pol;\ncreatepolicy.fractional.L2::evict_first.b64 pol, 1.0;\n"
                     "cp.async.cg.shared.global.L2::cache_hint [%0 + %2], [%1 + %3], 16, pol;\n}"
                     ::"r"(dst), "l"(src), "n"(J * 2048), "n"(J * SSTRIDE) : "memory");
        cp_steps<N, SSTRIDE, J + 1>(dst, src);
    }
}
template <int UNITS, int SSTRIDE>
__device__ __forceinline__ void burst(uint32_t dst, const char* src) {
#pragma unroll 1
    for (int i = 0; i < UNITS; i++) {
        cp_steps<4, SSTRIDE>(dst, src);
        dst += 4 * 2048;
        src += 4 * SSTRIDE;
    }
}
__device__ __forceinline__ uint32_t gtime32() { uint32_t t; asm volatile("mov.u32 %0, %%globaltimer_lo;" : "=r"(t)); return t; }
template <int N, int SSTRIDE>
__device__ __forceinline__ void paced_unit(uint32_t t0, int& due, uint32_t dst, const char* src) {
    while ((int)(gtime32() - t0) < due) {}
    due += N * TAU_NS;
    cp_steps<N, SSTRIDE>(dst, src);
    asm volatile("cp.async.commit_group;\ncp.async.wait_group %0;" ::"n"(WINDOW - 1) : "memory");
}
__device__ __forceinline__ void bar_comp() { asm volatile("bar.sync 1, 256;" ::: "memory"); }

__device__ __forceinline__ void ldsm4(uint32_t (&r)[4], uint32_t a) {
    asm volatile("ldmatrix.sync.aligned.m8n8.x4.shared.b16 {%0,%1,%2,%3}, [%4];"
                 : "=r"(r[0]), "=r"(r[1]), "=r"(r[2]), "=r"(r[3]) : "r"(a) : "memory");
}
__device__ __forceinline__ void ldsm4t(uint32_t (&r)[4], uint32_t a) {
    asm volatile("ldmatrix.sync.aligned.m8n8.x4.trans.shared.b16 {%0,%1,%2,%3}, [%4];"
                 : "=r"(r[0]), "=r"(r[1]), "=r"(r[2]), "=r"(r[3]) : "r"(a) : "memory");
}
__device__ __forceinline__ void mma16816(float (&c)[4], const uint32_t (&a)[4], uint32_t b0, uint32_t b1) {
    asm volatile("mma.sync.aligned.m16n8k16.row.col.f32.bf16.bf16.f32 {%0,%1,%2,%3}, {%4,%5,%6,%7}, {%8,%9}, {%0,%1,%2,%3};"
                 : "+f"(c[0]), "+f"(c[1]), "+f"(c[2]), "+f"(c[3])
                 : "r"(a[0]), "r"(a[1]), "r"(a[2]), "r"(a[3]), "r"(b0), "r"(b1));
}
__device__ __forceinline__ void mma1688(float (&c)[4], uint32_t a0, uint32_t a1, uint32_t b0) {
    asm volatile("mma.sync.aligned.m16n8k8.row.col.f32.bf16.bf16.f32 {%0,%1,%2,%3}, {%4,%5}, {%6}, {%0,%1,%2,%3};"
                 : "+f"(c[0]), "+f"(c[1]), "+f"(c[2]), "+f"(c[3])
                 : "r"(a0), "r"(a1), "r"(b0));
}
__device__ __forceinline__ void mma_tile64(float (&c0)[4], float (&c1)[4], uint32_t a, const uint32_t (&b0)[4], const uint32_t (&b1)[4]) {
    uint32_t f0[4], f1[4], f2[4], f3[4];
    ldsm4t(f0, a);
    ldsm4t(f1, a + 16 * 256);
    ldsm4t(f2, a + 32 * 256);
    ldsm4t(f3, a + 48 * 256);
    mma16816(c0, f0, b0[0], b0[1]);
    mma16816(c1, f1, b0[2], b0[3]);
    mma16816(c0, f2, b1[0], b1[1]);
    mma16816(c1, f3, b1[2], b1[3]);
}
__device__ __forceinline__ uint32_t pack_bf16(float lo, float hi) {
    uint32_t r;
    asm("cvt.rn.bf16x2.f32 %0, %1, %2;" : "=r"(r) : "f"(hi), "f"(lo));
    return r;
}
__device__ __forceinline__ float bf_lo(uint32_t v) { return __uint_as_float(v << 16); }
__device__ __forceinline__ float bf_hi(uint32_t v) { return __uint_as_float(v & 0xffff0000u); }
__device__ __forceinline__ float ex2(float x) { float y; asm("ex2.approx.ftz.f32 %0, %1;" : "=f"(y) : "f"(x)); return y; }
__device__ __forceinline__ float lg2(float x) { float y; asm("lg2.approx.ftz.f32 %0, %1;" : "=f"(y) : "f"(x)); return y; }
__device__ __forceinline__ float rcp(float x) { float y; asm("rcp.approx.ftz.f32 %0, %1;" : "=f"(y) : "f"(x)); return y; }
__device__ __forceinline__ float dot2(uint32_t a, uint32_t b, float acc) {
    return fmaf(bf_hi(a), bf_hi(b), fmaf(bf_lo(a), bf_lo(b), acc));
}
__device__ __forceinline__ void sts32(uint32_t a, uint32_t v) { asm volatile("st.shared.b32 [%0], %1;" ::"r"(a), "r"(v) : "memory"); }
__device__ __forceinline__ void sts16(uint32_t a, uint32_t v) { asm volatile("st.shared.b16 [%0], %1;" ::"r"(a), "h"((unsigned short)v) : "memory"); }

__device__ __forceinline__ void ll_store(unsigned long long* p, uint32_t payload, uint32_t epoch) {
    asm volatile("{\n.reg .b64 v;\nmov.b64 v, {%1, %2};\nst.relaxed.gpu.global.b64 [%0], v;\n}" ::"l"(p), "r"(payload), "r"(epoch) : "memory");
}
__device__ __forceinline__ uint2 ll_load(const unsigned long long* p) {
    uint2 v;
    asm volatile("{\n.reg .b64 v;\nld.relaxed.gpu.global.b64 v, [%2];\nmov.b64 {%0, %1}, v;\n}" : "=r"(v.x), "=r"(v.y) : "l"(p) : "memory");
    return v;
}
template <int N, int STRIDE, int SLEEP>
__device__ __forceinline__ void ll_finish(uint2 (&v)[N], const unsigned long long* p, uint32_t epoch) {
#pragma unroll 1
    for (int it = 0; it < SPIN_LIMIT; it++) {
        bool ok = true;
#pragma unroll
        for (int i = 0; i < N; i++) ok = ok && v[i].y == epoch;
        if (__all_sync(0xffffffffu, ok)) break;
        if (SLEEP) __nanosleep(SLEEP);
#pragma unroll
        for (int i = 0; i < N; i++)
            if (v[i].y != epoch) v[i] = ll_load(p + i * STRIDE);
    }
}

__device__ __forceinline__ void delay(uint32_t cycles) {
    const uint32_t c0 = (uint32_t)clock();
    while ((uint32_t)clock() - c0 < cycles) {}
}

constexpr float LOG2E = 1.4426950408889634f;
__device__ __forceinline__ float mish(float h) {
    const float e = ex2(-fabsf(h) * LOG2E);
    const float num = h >= 0.f ? fmaf(2.f, e, 1.f) : e * (e + 2.f);
    const float den = num + (h >= 0.f ? 2.f * e * e : 2.f);
    return h * num * rcp(den);
}

__device__ __forceinline__ void loader(const __nv_bfloat16* __restrict__ kc, const __nv_bfloat16* __restrict__ vc,
                                    const __nv_bfloat16* __restrict__ wq, const __nv_bfloat16* __restrict__ wo,
                                    const __nv_bfloat16* __restrict__ w1, const __nv_bfloat16* __restrict__ w2, uint32_t sb) {
    const int cta = blockIdx.x;
    const int kvh = cta >> 4, r = cta & 15;
    const int hj = cta >> 2, cq = cta & 3;
    const uint32_t bar0 = sb + OFF_BAR;
    {
        const int lt = threadIdx.x;
        const uint32_t t0 = gtime32();
        burst<4, 32 * HQD * 2>(sb + OFF_WQ + (lt >> 2) * 64 + (((lt & 3) ^ ((lt >> 3) & 3)) << 4),
                               (const char*)wq + (size_t)(lt >> 2) * (HQD * 2) + cta * 64 + (lt & 3) * 16);
        if (cta < 112)
            burst<2, 64 * FF * 2>(sb + OFF_W1 + (lt >> 1) * 32 + (((lt & 1) ^ ((lt >> 3) & 1)) << 4),
                                  (const char*)w1 + (size_t)(lt >> 1) * (FF * 2) + cta * 32 + (lt & 1) * 16);
        asm volatile("cp.async.commit_group;" ::: "memory");
        if (lt <= BAR_FREE) mbar_init(bar0 + 8 * lt, lt == BAR_FREE ? 8 : NLOAD);
        asm volatile("bar.sync 2, 128;\nbar.arrive 0, 384;" ::: "memory");
        const int row = lt >> 4, c = lt & 15;
        const uint32_t sw = sb + row * 256 + ((c ^ row) << 4);
        const size_t kvoff = ((size_t)((r >> 2) * 8 + kvh) * SK + (SK - WIN)) * 256 + (r & 3) * 8192 + lt * 16;
        int due = T_K;
        cp_arrive(bar0 + 8 * BAR_WQ);
        {
            uint32_t dst = sw + OFF_K;
            const char* src = (const char*)kc + kvoff;
#pragma unroll 1
            for (int u = 0; u < 16; u++) {
                paced_unit<4, 2048>(t0, due, dst, src);
                dst += 8192;
                src = u == 7 ? (const char*)vc + kvoff : src + 4 * 8192;
                if (u >= 7 && (u & 1)) cp_arrive(bar0 + 8 * (BAR_K + ((u - 7) >> 1)));
            }
        }
        mbar_wait(bar0 + 8 * BAR_FREE);
        const int wofs = row * (DM * 2) + cq * 256 + c * 16;
        {
            const char* src = (const char*)w2 + hj * (56 * DM * 2) + wofs;
            paced_unit<4, 8 * DM * 2>(t0, due, sw + OFF_W2, src);
            paced_unit<3, 8 * DM * 2>(t0, due, sw + OFF_W2 + 4 * 2048, src + 4 * 8 * DM * 2);
            cp_arrive(bar0 + 8 * BAR_W2);
        }
        {
            uint32_t dst = sw + OFF_WO;
            const char* src = (const char*)wo + hj * (128 * DM * 2) + wofs;
#pragma unroll 1
            for (int u = 0; u < 4; u++) {
                paced_unit<4, 8 * DM * 2>(t0, due, dst, src);
                dst += 8192;
                src += 32 * DM * 2;
                if (u >= 1) cp_arrive(bar0 + 8 * (BAR_WO0 + u - 1));
            }
        }
        asm volatile("cp.async.wait_all;" ::: "memory");
    }
}

__global__ void __launch_bounds__(NTHREADS, 1)
fused_decode_kernel(const __nv_bfloat16* __restrict__ x, const __nv_bfloat16* __restrict__ kc,
                    const __nv_bfloat16* __restrict__ vc, const __nv_bfloat16* __restrict__ wq,
                    const __nv_bfloat16* __restrict__ wo, const __nv_bfloat16* __restrict__ w1,
                    const __nv_bfloat16* __restrict__ b1, const __nv_bfloat16* __restrict__ w2,
                    const __nv_bfloat16* __restrict__ gw, __nv_bfloat16* __restrict__ out) {
    extern __shared__ __align__(128) unsigned char smem[];
    const uint32_t sb = smem_u32(smem);
    const int cta = blockIdx.x;
    const int kvh = cta >> 4, r = cta & 15;
    const int hj = cta >> 2, cq = cta & 3;
    const uint32_t bar0 = sb + OFF_BAR;

    if (threadIdx.x < NLOAD) {
        loader(kc, vc, wq, wo, w1, w2, sb);
        return;
    }

    const int tid = threadIdx.x - NLOAD;
    const int lane = tid & 31, w = tid >> 5;
    const int g = lane >> 2, t = lane & 3;
    const int t1 = t & 1, th = t >> 1;
    const int mi = lane >> 3, l8 = lane & 7;
    const int ab = r >> 2;
    float* const part = reinterpret_cast<float*>(smem + OFF_PART);
    float* const wmax = reinterpret_cast<float*>(smem + OFF_RED);
    float* const wsum = wmax + 32;
    float* const gpart = wmax + 64;
    unsigned long long* const mail = g_mail;

    const uint4 xv = __ldg(reinterpret_cast<const uint4*>(x) + tid);
    const uint4 gv = __ldg(reinterpret_cast<const uint4*>(gw) + (tid & 63));
    const uint32_t epoch = *(volatile unsigned int*)&mail[MB_EP + cta] + 1u;
    const uint32_t b1v = __ldg(reinterpret_cast<const uint32_t*>(b1 + (cta < 112 ? cta : 0) * 16) + (tid & 7));
    const uint32_t tag16 = epoch % 65535u + 1u;
    const int hb = 2 * t1 + th;
    unsigned long long* const ox_slot = mail + MB_OX + ((kvh * 4 + hb) * 16 + r) * 64 + w * 8 + g;
    unsigned long long* e4_slot = mail + MB_E4 + ((cq * 8 + w) * 32 + hj) * 32 + hb * 8 + g;
    const unsigned long long* ep = mail + MB_E4 + ((cq * 8 + (hj & 7)) * 32 + w * 4 + (lane >> 3)) * 32 + (hj >> 3) * 8 + (lane & 7);
    __nv_bfloat16* outp = out + (hj >> 3) * DM + cq * 128 + (hj & 7) * 16 + (tid & 15);
    uint32_t fin_st = sb + OFF_PART + (w * 16 + (lane & 7)) * 4, fin_ld = sb + OFF_PART + (tid & 15) * 4;
    asm volatile("" : "+l"(e4_slot), "+l"(ep), "+l"(outp), "+r"(fin_st), "+r"(fin_ld));
    *reinterpret_cast<uint4*>(smem + OFF_XS + (tid >> 6) * 1040 + (tid & 63) * 16) = xv;
    {
        float acc = dot2(xv.w, gv.w, dot2(xv.z, gv.z, dot2(xv.y, gv.y, dot2(xv.x, gv.x, 0.f))));
#pragma unroll
        for (int o = 16; o > 0; o >>= 1) acc += __shfl_xor_sync(0xffffffffu, acc, o);
        if (lane == 0) gpart[w] = acc;
    }
    asm volatile("bar.sync 0, 384;" ::: "memory");
    ll_store(ox_slot, 0u, 0u);
    ll_store(e4_slot, 0u, 0u);

    {
        uint32_t xb[2][4];
        const uint32_t xa = sb + OFF_XS + (l8 & 3) * 1040 + (w * 64 + mi * 8) * 2;
        ldsm4(xb[0], xa);
        ldsm4(xb[1], xa + 64);
        const int kr = w * 64 + l8 + ((mi >> 1) << 3);
        const uint32_t aq0 = sb + OFF_WQ + kr * 64 + (((mi & 1) ^ ((kr >> 1) & 3)) << 4);
        const uint32_t aq1 = aq0 ^ 32;
        const uint32_t ah = sb + OFF_W1 + kr * 32 + (((mi & 1) ^ ((kr >> 2) & 1)) << 4);
        float cq0[4] = {0.f, 0.f, 0.f, 0.f}, cq1[4] = {0.f, 0.f, 0.f, 0.f}, ch[4] = {0.f, 0.f, 0.f, 0.f};
        mbar_wait(bar0 + 8 * BAR_WQ);
#pragma unroll
        for (int ks = 0; ks < 4; ks++) {
            uint32_t a0[4], a1[4], a2[4];
            ldsm4t(a0, aq0 + ks * 1024);
            ldsm4t(a1, aq1 + ks * 1024);
            ldsm4t(a2, ah + ks * 512);
            const uint32_t bb0 = xb[ks >> 1][(ks & 1) * 2], bb1 = xb[ks >> 1][(ks & 1) * 2 + 1];
            mma16816(cq0, a0, bb0, bb1);
            mma16816(cq1, a1, bb0, bb1);
            mma16816(ch, a2, bb0, bb1);
        }
        __syncwarp();
        if (lane == 0) mbar_arrive(bar0 + 8 * BAR_FREE);
        if (t < 2) {
            float* p0 = part + (w * 4 + 2 * t) * 48 + g;
            p0[0] = cq0[0]; p0[48] = cq0[1]; p0[8] = cq0[2]; p0[56] = cq0[3];
            p0[16] = cq1[0]; p0[64] = cq1[1]; p0[24] = cq1[2]; p0[72] = cq1[3];
            p0[32] = ch[0]; p0[80] = ch[1]; p0[40] = ch[2]; p0[88] = ch[3];
        }
        bar_comp();
        if (tid < 96) {
            const bool isq = tid < 64;
            const int b = isq ? tid >> 4 : (tid - 64) >> 3;
            const int cp = isq ? tid & 15 : 16 + (tid & 7);
            float v0 = 0.f, v1 = 0.f;
#pragma unroll
            for (int i = 0; i < 8; i++) {
                const float2 v = *reinterpret_cast<const float2*>(part + (i * 4 + b) * 48 + 2 * cp);
                v0 += v.x; v1 += v.y;
            }
            if (!isq) { v0 = mish(v0 + bf_lo(b1v)); v1 = mish(v1 + bf_hi(b1v)); }
            const int slot = isq ? MB_QX + (kvh * 4 + b) * 256 + r * 16 + cp : MB_AX + cta * 32 + (tid - 64);
            if (isq || cta < 112) ll_store(mail + slot, pack_bf16(v0, v1), epoch);
        }
    }
    mbar_wait(bar0 + 8 * BAR_K);
    {
        const unsigned long long* qp = mail + MB_QX + (kvh * 4 + ab) * 256 + tid;
        uint2 v[1] = {ll_load(qp)};
        ll_finish<1, 1, BACKOFF_NS>(v, qp, epoch);
        sts32(sb + OFF_QS + (tid >> 6) * 272 + (tid & 63) * 4, v[0].x);
    }
    bar_comp();
    constexpr float SC = 0.08838834764831845f * LOG2E;
    {
        float s0[4] = {0.f, 0.f, 0.f, 0.f}, s1[4] = {0.f, 0.f, 0.f, 0.f};
        const uint32_t qa = sb + OFF_QS + (l8 & 3) * 272 + mi * 16;
        const uint32_t kb = sb + OFF_K + (w * 32 + (lane & 15)) * 256;
        const int kx = (lane >> 4) ^ l8;
#pragma unroll 1
        for (int i = 0; i < 4; i++) {
            uint32_t qb[4], a0[4], a1[4], a2[4], a3[4];
            const uint32_t o0 = (uint32_t)((kx ^ (4 * i)) << 4), o1 = o0 ^ 32;
            ldsm4(qb, qa + i * 64);
            ldsm4(a0, kb + o0);
            ldsm4(a1, kb + 16 * 256 + o0);
            ldsm4(a2, kb + o1);
            ldsm4(a3, kb + 16 * 256 + o1);
            mma16816(s0, a0, qb[0], qb[1]);
            mma16816(s1, a1, qb[0], qb[1]);
            mma16816(s0, a2, qb[2], qb[3]);
            mma16816(s1, a3, qb[2], qb[3]);
        }
        float m0 = fmaxf(fmaxf(s0[0], s0[2]), fmaxf(s1[0], s1[2]));
        float m1 = fmaxf(fmaxf(s0[1], s0[3]), fmaxf(s1[1], s1[3]));
#pragma unroll
        for (int o = 4; o < 32; o <<= 1) {
            m0 = fmaxf(m0, __shfl_xor_sync(0xffffffffu, m0, o));
            m1 = fmaxf(m1, __shfl_xor_sync(0xffffffffu, m1, o));
        }
        if (lane < 2) *reinterpret_cast<float2*>(wmax + w * 4 + 2 * lane) = make_float2(m0, m1);
        bar_comp();
#pragma unroll
        for (int i = 0; i < 8; i++) {
            const float2 v = *reinterpret_cast<const float2*>(wmax + i * 4 + 2 * t1);
            m0 = fmaxf(m0, v.x); m1 = fmaxf(m1, v.y);
        }
        const float n0 = m0 * SC, n1 = m1 * SC;
        const uint32_t pa = pack_bf16(ex2(fmaf(th ? s1[0] : s0[0], SC, -n0)), ex2(fmaf(th ? s1[2] : s0[2], SC, -n0)));
        const uint32_t pb = pack_bf16(ex2(fmaf(th ? s1[1] : s0[1], SC, -n1)), ex2(fmaf(th ? s1[3] : s0[3], SC, -n1)));
        const uint32_t pd = sb + OFF_PS + t1 * (2 * 528) + (w * 32 + th * 16 + g) * 2;
        sts16(pd, pa); sts16(pd + 16, pa >> 16); sts16(pd + 528, pb); sts16(pd + 544, pb >> 16);
        float l0 = bf_lo(pa) + bf_hi(pa), l1 = bf_lo(pb) + bf_hi(pb);
#pragma unroll
        for (int o = 2; o < 32; o <<= 1) {
            l0 += __shfl_xor_sync(0xffffffffu, l0, o);
            l1 += __shfl_xor_sync(0xffffffffu, l1, o);
        }
        if (lane < 2) *reinterpret_cast<float2*>(wsum + w * 4 + 2 * lane) = make_float2(l0, l1);
        bar_comp();
    }
    const uint32_t a_off = (l8 + ((mi >> 1) << 3)) * 256 + (((2 * w + (mi & 1)) ^ l8) << 4);
    {
        const int hd = (lane >> 2) & 3;
        float l = 0.f, m = wmax[hd];
#pragma unroll
        for (int i = 0; i < 8; i++) { l += wsum[i * 4 + hd]; m = fmaxf(m, wmax[i * 4 + hd]); }
        m *= SC;
        const unsigned long long* lp = mail + MB_LX + ((cta & ~3) + t) * 16 + hd;
        if (tid < 16 && t == cq) ll_store(const_cast<unsigned long long*>(lp), __float_as_uint(m + lg2(l)), epoch);
        if (w >= 4) {
            const int b = w - 4, e = min(lane, 27), ge = hj * 28 + e;
            const unsigned long long* ap = mail + MB_AX + (ge >> 3) * 32 + b * 8 + (ge & 7);
            uint2 av[1] = {ll_load(ap)};
            ll_finish<1, 1, BACKOFF_NS>(av, ap, epoch);
            sts32(sb + OFF_AS + b * 144 + e * 4, av[0].x);
        }
        float o0[4] = {0.f, 0.f, 0.f, 0.f}, o1[4] = {0.f, 0.f, 0.f, 0.f};
        const uint32_t pb = sb + OFF_PS + (l8 & 3) * 528 + mi * 16;
        uint2 lv[1];
        float wgt;
#pragma unroll 1
        for (int ch = 0; ch < 4; ch++) {
            uint32_t pf0[4], pf1[4];
            ldsm4(pf0, pb + ch * 128);
            ldsm4(pf1, pb + ch * 128 + 64);
            if (ch == 2) lv[0] = ll_load(lp);
            if (ch == 3) {
                ll_finish<1, 1, BACKOFF_NS>(lv, lp, epoch);
                const float e = __uint_as_float(lv[0].x);
                float mx = fmaxf(e, __shfl_xor_sync(0xffffffffu, e, 1));
                mx = fmaxf(mx, __shfl_xor_sync(0xffffffffu, mx, 2));
                float den = ex2(e - mx);
                den += __shfl_xor_sync(0xffffffffu, den, 1);
                den += __shfl_xor_sync(0xffffffffu, den, 2);
                wgt = __shfl_sync(0xffffffffu, ex2(m - mx) * rcp(den), hb * 4);
            }
            mbar_wait(bar0 + 8 * (BAR_V0 + ch));
            mma_tile64(o0, o1, sb + OFF_V + ch * 16384 + a_off, pf0, pf1);
        }
        const float va = (th ? o0[1] + o1[1] : o0[0] + o1[0]) * wgt;
        const float vb = (th ? o0[3] + o1[3] : o0[2] + o1[2]) * wgt;
        ll_store(ox_slot, pack_bf16(va, vb), epoch);
    }
    {
        const unsigned long long* op = mail + MB_OX + (hj * 16 + (tid >> 6) * 4) * 64 + (tid & 63);
        uint2 ov[4];
        bar_comp();
        float bq[4] = {0.f, 0.f, 0.f, 0.f}, b2[4] = {0.f, 0.f, 0.f, 0.f};
        {
            uint32_t af0[4], af1[4], f0[4], f1[4], f2[4], f3[4];
            const uint32_t aa = sb + OFF_AS + (l8 & 3) * 144 + mi * 16;
            ldsm4(af0, aa);
            ldsm4(af1, aa + 64);
            mbar_wait(bar0 + 8 * BAR_W2);
            const uint32_t wb = sb + OFF_W2 + a_off;
            ldsm4t(f0, wb);
            ldsm4t(f1, wb + 16 * 256);
            ldsm4t(f2, wb + 32 * 256);
            ldsm4t(f3, wb + 48 * 256);
            mma16816(bq, f0, af0[0], af0[1]);
            mma16816(b2, f1, af0[2], af0[3]);
            mma16816(bq, f2, af1[0], af1[1]);
            mma1688(b2, f3[0], f3[1], af1[2]);
        }
        const float gt = rcp(1.f + ex2(-(gpart[2 * hb] + gpart[2 * hb + 1]) * LOG2E));
        const float rb = (1.f - gt) * (th ? bq[1] + b2[1] : bq[0] + b2[0]);
        const float rd = (1.f - gt) * (th ? bq[3] + b2[3] : bq[2] + b2[2]);
        delay(O_FIRST);
#pragma unroll
        for (int s = 0; s < 4; s++) ov[s] = ll_load(op + s * 64);
        ll_finish<4, 64, BACKOFF_NS>(ov, op, epoch);
        {
            const float v0 = (bf_lo(ov[0].x) + bf_lo(ov[1].x)) + (bf_lo(ov[2].x) + bf_lo(ov[3].x));
            const float v1 = (bf_hi(ov[0].x) + bf_hi(ov[1].x)) + (bf_hi(ov[2].x) + bf_hi(ov[3].x));
            const uint32_t pk = pack_bf16(v0, v1);
            const uint32_t od = sb + OFF_OS + (tid >> 6) * 272 + (tid & 56) * 4 + (tid & 7) * 2;
            sts16(od, pk); sts16(od + 16, pk >> 16);
        }
        bar_comp();
        uint32_t of[4][4];
        const uint32_t fb = sb + OFF_OS + (l8 & 3) * 272 + mi * 16;
#pragma unroll
        for (int i = 0; i < 4; i++) ldsm4(of[i], fb + i * 64);
        float a0[4] = {0.f, 0.f, 0.f, 0.f}, a1[4] = {0.f, 0.f, 0.f, 0.f};
        mbar_wait(bar0 + 8 * BAR_WO0);
        mma_tile64(a0, a1, sb + OFF_WO + a_off, of[0], of[1]);
        uint32_t f0[4], f1[4];
        mbar_wait(bar0 + 8 * BAR_WO1);
        ldsm4t(f0, sb + OFF_WO + 64 * 256 + a_off);
        ldsm4t(f1, sb + OFF_WO + 80 * 256 + a_off);
        mma16816(a0, f0, of[2][0], of[2][1]);
        mma16816(a1, f1, of[2][2], of[2][3]);
        mbar_wait(bar0 + 8 * BAR_WO2);
        ldsm4t(f0, sb + OFF_WO + 96 * 256 + a_off);
        ldsm4t(f1, sb + OFF_WO + 112 * 256 + a_off);
        mma16816(a0, f0, of[3][0], of[3][1]);
        mma16816(a1, f1, of[3][2], of[3][3]);
        const uint32_t r0 = __float_as_uint(fmaf(gt, th ? a0[1] + a1[1] : a0[0] + a1[0], rb)) + 0x80u;
        const uint32_t r1 = __float_as_uint(fmaf(gt, th ? a0[3] + a1[3] : a0[2] + a1[2], rd)) + 0x80u;
        ll_store(e4_slot, ((r1 << 8) & 0xffff0000u) | tag16, (r0 & 0xffffff00u) | (r1 >> 24));
    }
    {
        uint2 v;
        {
            delay(E4_FIRST);
            v = ll_load(ep);
#pragma unroll 1
            for (int it = 0; it < SPIN_LIMIT; it++) {
                if (__all_sync(0xffffffffu, (v.x & 0xffffu) == tag16)) break;
                if ((v.x & 0xffffu) != tag16) v = ll_load(ep);
            }
        }
        float s0 = __uint_as_float(v.y & 0xffffff00u), s1 = __uint_as_float((v.y << 24) | ((v.x & 0xffff0000u) >> 8));
        s0 += __shfl_xor_sync(0xffffffffu, s0, 8);
        s1 += __shfl_xor_sync(0xffffffffu, s1, 8);
        s0 += __shfl_xor_sync(0xffffffffu, s0, 16);
        s1 += __shfl_xor_sync(0xffffffffu, s1, 16);
        if (lane < 8) { sts32(fin_st, __float_as_uint(s0)); sts32(fin_st + 32, __float_as_uint(s1)); }
        bar_comp();
        if (tid < 16) {
            float p[8];
#pragma unroll
            for (int i = 0; i < 8; i++) asm volatile("ld.shared.f32 %0, [%1];" : "=f"(p[i]) : "r"(fin_ld + i * 64) : "memory");
            *outp = __float2bfloat16(((p[0] + p[1]) + (p[2] + p[3])) + ((p[4] + p[5]) + (p[6] + p[7])));
            if (tid == 0) *(volatile unsigned int*)&mail[MB_EP + cta] = epoch;
        }
    }
}

}

extern "C" void kernel_launch(void* const* d_in, const int* in_sizes, int n_in, void* d_out, int out_size) {
    (void)in_sizes; (void)n_in; (void)out_size;
    const __nv_bfloat16* x  = (const __nv_bfloat16*)d_in[0];
    const __nv_bfloat16* kc = (const __nv_bfloat16*)d_in[1];
    const __nv_bfloat16* vc = (const __nv_bfloat16*)d_in[2];
    const __nv_bfloat16* wq = (const __nv_bfloat16*)d_in[3];
    const __nv_bfloat16* wo = (const __nv_bfloat16*)d_in[4];
    const __nv_bfloat16* w1 = (const __nv_bfloat16*)d_in[6];
    const __nv_bfloat16* b1 = (const __nv_bfloat16*)d_in[7];
    const __nv_bfloat16* w2 = (const __nv_bfloat16*)d_in[8];
    const __nv_bfloat16* gw = (const __nv_bfloat16*)d_in[9];
    cudaFuncSetAttribute(fused_decode_kernel, cudaFuncAttributeMaxDynamicSharedMemorySize, SMEM_BYTES);
    fused_decode_kernel<<<NCTA, NTHREADS, SMEM_BYTES, cudaStreamPerThread>>>(x, kc, vc, wq, wo, w1, b1, w2, gw,
                                                                            (__nv_bfloat16*)d_out);
}
```
